```python
import torch

def _softmax(x, axis=-1):
    return torch.softmax(x, dim=axis)
def _gelu(x):
    return torch.nn.functional.gelu(x, approximate="tanh")
def _silu(x):
    return torch.nn.functional.silu(x)
def _sigmoid(x):
    return torch.sigmoid(x)
def _layernorm(x, axis=-1, eps=1e-5):
    m = x.mean(dim=axis, keepdim=True)
    v = x.var(dim=axis, keepdim=True, unbiased=False)
    return (x - m) / torch.sqrt(v + eps)
def _scatter_add(tgt, idx, src, axis=0):
    return tgt.clone().index_add_(axis, idx, src)
def _segment_sum(src, seg, n):
    out = torch.zeros((n,) + src.shape[1:], dtype=src.dtype)
    return out.index_add_(0, seg, src)
def _pad(x, pw):
    flat = tuple(v for pair in reversed(pw) for v in pair)
    return torch.nn.functional.pad(x, flat)

kernel_name = 'sequential_preLN__linear_kernel_hedgehog__dense_activation_relu__prompt'

def setup_inputs():

    _w = (lambda a: (lambda t: t.to(torch.bfloat16) if t.is_floating_point() else t)(torch.as_tensor(a)))
    def _A_setup():
        B, S, D, H = 1, 2048, 640, 32
        Dh = D // H
        return {
            "x": _w((lambda *s: torch.randn(*s, dtype=torch.bfloat16) * 0.05)(B, S, D)),
            "wqkv": _w((lambda *s: torch.randn(*s, dtype=torch.bfloat16) * 0.2)(D, 3 * D)),
            "w_phi": _w((lambda *s: torch.randn(*s, dtype=torch.bfloat16) * 0.2)(H, Dh, Dh) * (Dh ** -0.5)),
            "wo": _w((lambda *s: torch.randn(*s, dtype=torch.bfloat16) * 0.05)(D, D)),
        }
    _A_in = _A_setup()

    def _B_setup():
        B, S, D, Dff = 1, 2048, 640, 1728
        return {
            "x": _w((lambda *s: torch.randn(*s, dtype=torch.bfloat16) * 0.05)(B, S, D)),
            "w1": _w((lambda *s: torch.randn(*s, dtype=torch.bfloat16) * 0.05)(D, Dff)),
            "w2": _w((lambda *s: torch.randn(*s, dtype=torch.bfloat16) * 0.05)(Dff, D)),
        }
    _B_in = _B_setup()

    return {
        "A_x": _A_in["x"],
        "A_wqkv": _A_in["wqkv"],
        "A_w_phi": _A_in["w_phi"],
        "A_wo": _A_in["wo"],
        "B_x": _B_in["x"],
        "B_w1": _B_in["w1"],
        "B_w2": _B_in["w2"],
    }

def reference(A_x, A_wqkv, A_w_phi, A_wo, B_x, B_w1, B_w2):
    def _A_ref(x, wqkv, w_phi, wo):
        B, S, D = x.shape
        H = 32; Dh = D // H
        qkv = (lambda x, *d: x.permute(*d))((x @ wqkv).reshape(B, S, 3, H, Dh), 2, 0, 3, 1, 4)
        q, k, v = qkv[0], qkv[1], qkv[2]
        pq = torch.einsum("bhsd,hdf->bhsf", q, w_phi)
        pk = torch.einsum("bhsd,hdf->bhsf", k, w_phi)
        phi_q = torch.concatenate([_softmax(pq, axis=-1), _softmax(-pq, axis=-1)], axis=-1)
        phi_k = torch.concatenate([_softmax(pk, axis=-1), _softmax(-pk, axis=-1)], axis=-1)
        kv = torch.einsum("bhsf,bhsd->bhfd", phi_k, v)
        z  = torch.einsum("bhsf->bhf", phi_k)
        num = torch.einsum("bhqf,bhfd->bhqd", phi_q, kv)
        den = torch.einsum("bhqf,bhf->bhq", phi_q, z)[..., None] + 1e-6
        o = num / den
        return (lambda x, *d: x.permute(*d))(o, 0, 2, 1, 3).reshape(B, S, D) @ wo

    def _B_ref(x, w1, w2):
        h = torch.einsum("bsd,df->bsf", x, w1)
        zero = torch.zeros_like(h)
        h = torch.maximum(h, zero)
        return torch.einsum("bsf,fd->bsd", h, w2)

    x = A_x
    h = x + _A_ref(_layernorm(x, axis=-1), A_wqkv, A_w_phi, A_wo)
    h2 = h + _B_ref(_layernorm(h, axis=-1), B_w1, B_w2)
    return h2
```

```cpp
#include <cuda_runtime.h>
#include <cuda_bf16.h>
#include <cuda.h>
#include <stdint.h>

#define CS_KB 0
#define HREG 72
#define CREG 216
#define A_PP 1
#define W_FL 2
#define ORS 0
#define HRS 0
#define OHS 1
#define SPARE 2
#define F2_PP 1
#define PF_KB 4
#define HH_BY_SM 1
#define HH_DEBUG 0

namespace hh {

constexpr int kFF = 1728;
constexpr uint32_t KB = 1024;

constexpr uint32_t OFF_X    = 192 * KB;
constexpr uint32_t OFF_WPHI = OFF_X;
constexpr uint32_t OFF_KVB  = OFF_X + 12800;
constexpr uint32_t OFF_XT   = OFF_X + 8 * KB;
constexpr uint32_t OFF_STG  = OFF_X;
constexpr uint32_t OFF_CS   = OFF_X + 31232;
constexpr uint32_t OFF_BAR  = OFF_CS + 960;
constexpr uint32_t OFF_PHIK = 0, OFF_V = 48 * KB;

enum : int {
  B_FA = 0, B_FW = 10, B_FF = 20, B_FG = 30,
  B_EA = 40, B_EF = 50, B_EW = 60  ,
  B_KVFREE = 64, B_HGO = 65,
  B_DS = 70  ,
  B_EG = 80  , B_KVST = 86,
  B_FX = 87, B_CS = 88, B_DONE = 89, B_KVZ = 90, B_HZ = 91, B_COUNT = 92
};
constexpr uint32_t SMEM_BYTES = OFF_BAR + B_COUNT * 8 + 16 + (HH_DEBUG ? 288 : 0);
static_assert(SMEM_BYTES <= 232448, "smem");

constexpr size_t PAGE = 2u << 20;
__device__ uint4 g_arena[10 * PAGE / 16];
__device__ __forceinline__ uint8_t* a_row(uint8_t* a, int i) { return a + (i >> 2) * PAGE + (i & 3) * (340 * KB); }
__device__ __forceinline__ uint4* a_of(uint8_t* a, int i) { return (uint4*)a_row(a, i); }
__device__ __forceinline__ uint4* a_hf(uint8_t* a, int i) { return (uint4*)(a_row(a, i) + 160 * KB); }
__device__ __forceinline__ uint4* a_hst(uint8_t* a, int i) { return (uint4*)(a_row(a, i) + 320 * KB); }
__device__ __forceinline__ uint32_t* a_hint_o(uint8_t* a, int i) { return (uint32_t*)(a_row(a, i) + 328 * KB); }
__device__ __forceinline__ uint32_t* a_hint_p(uint8_t* a, int i) { return (uint32_t*)(a_row(a, i) + 336 * KB); }
__device__ __forceinline__ uint4* a_part(uint8_t* a, int i) {
  return (uint4*)(a + (i >> 2) * PAGE + ((i & 3) == 3 ? 1360 * KB : 5 * PAGE + (i & 3) * (640 * KB)));
}
__device__ __forceinline__ uint4* a_kvp(uint8_t* a) { return (uint4*)(a + 4 * PAGE); }
__device__ __forceinline__ uint4* a_kvf(uint8_t* a) { return (uint4*)(a + 4 * PAGE + 1024 * KB); }
__device__ __forceinline__ uint4* a_csp(uint8_t* a) { return (uint4*)(a + 4 * PAGE + 1088 * KB); }
__device__ __forceinline__ uint32_t* a_epoch(uint8_t* a) { return (uint32_t*)(a + 4 * PAGE + 1152 * KB); }
#define TSTAMP(k) do { } while (0)
#define TSTAMP2(k) do { } while (0)

struct Params {
  CUtensorMap x, xt, wqkv_main, wqkv_tail, wo, w1_main, w1_half, w2_main, w2_half, out_st;
  const __nv_bfloat16 *px, *pwqkv, *pwphi, *pwo, *pw1, *pw2;
  uint8_t* arena;
};

__device__ __forceinline__ void mbar_init(uint32_t bar, uint32_t cnt) { asm volatile("mbarrier.init.shared::cta.b64 [%0], %1;" ::"r"(bar), "r"(cnt) : "memory"); }
__device__ __forceinline__ void mbar_expect(uint32_t bar, uint32_t bytes) { asm volatile("mbarrier.arrive.expect_tx.shared::cta.b64 _, [%0], %1;" ::"r"(bar), "r"(bytes) : "memory"); }
__device__ __forceinline__ void mbar_arrive(uint32_t bar) { asm volatile("mbarrier.arrive.shared::cta.b64 _, [%0];" ::"r"(bar) : "memory"); }
__device__ __forceinline__ void mbar_wait(uint32_t bar) {
  asm volatile(
      "{ .reg .pred p;\n"
      "HH_WAIT:\n"
      "mbarrier.try_wait.parity.shared::cta.b64 p, [%0], 0;\n"
      "@!p bra HH_WAIT;\n"
      "}" ::"r"(bar) : "memory");
}
__device__ __forceinline__ void mbar_wait_bounded(uint32_t bar) {
  asm volatile(
      "{ .reg .pred p, q; .reg .u32 t0, t1;\n"
      "mbarrier.try_wait.parity.shared::cta.b64 p, [%0], 0;\n"
      "@p bra HH_OK;\n"
      "mov.u32 t0, %globaltimer_lo;\n"
      "HH_WAITB:\n"
      "mbarrier.try_wait.parity.shared::cta.b64 p, [%0], 0;\n"
      "@p bra HH_OK;\n"
      "mov.u32 t1, %globaltimer_lo;\n"
      "sub.u32 t1, t1, t0;\n"
      "setp.gt.u32 q, t1, 2000000000;\n"
      "@q trap;\n"
      "bra HH_WAITB;\n"
      "HH_OK:\n"
      "}" ::"r"(bar) : "memory");
}
__device__ __forceinline__ void watchdog(uint32_t bar) {
  asm volatile(
      "{ .reg .pred p, q; .reg .u64 t0, t1;\n"
      "mov.u64 t0, %globaltimer;\n"
      "HH_DOG:\n"
      "mbarrier.try_wait.parity.shared::cta.b64 p, [%0], 0, 2000;\n"
      "mov.u64 t1, %globaltimer;\n"
      "sub.u64 t1, t1, t0;\n"
      "setp.gt.u64 q, t1, 2000000000;\n"
      "@q trap;\n"
      "@!p bra HH_DOG;\n"
      "}" ::"r"(bar) : "memory");
}
__device__ __forceinline__ void tma2d(uint32_t dst, const CUtensorMap* tm, uint32_t bar, int c0, int c1) {
  asm volatile("cp.async.bulk.tensor.2d.shared::cluster.global.mbarrier::complete_tx::bytes [%0], [%1, {%3, %4}], [%2];" ::"r"(dst), "l"(tm), "r"(bar), "r"(c0), "r"(c1) : "memory");
}
__device__ __forceinline__ void tma3d(uint32_t dst, const CUtensorMap* tm, uint32_t bar, int c0, int c1, int c2) {
  asm volatile("cp.async.bulk.tensor.3d.shared::cluster.global.mbarrier::complete_tx::bytes [%0], [%1, {%3, %4, %5}], [%2];" ::"r"(dst), "l"(tm), "r"(bar), "r"(c0), "r"(c1), "r"(c2) : "memory");
}
__device__ __forceinline__ void tma_store2d(const CUtensorMap* tm, uint32_t src, int c0, int c1) {
  asm volatile("cp.async.bulk.tensor.2d.global.shared::cta.bulk_group [%0, {%2, %3}], [%1];" ::"l"(tm), "r"(src), "r"(c0), "r"(c1) : "memory");
}
__device__ __forceinline__ void bulk_commit() { asm volatile("cp.async.bulk.commit_group;" ::: "memory"); }
__device__ __forceinline__ void bulk_wait0() { asm volatile("cp.async.bulk.wait_group 0;" ::: "memory"); }
__device__ __forceinline__ void l2_prefetch(const void* p, uint32_t bytes) { asm volatile("cp.async.bulk.prefetch.L2.global [%0], %1;" ::"l"(p), "r"(bytes) : "memory"); }
__device__ __forceinline__ void prefetch_tmap(const CUtensorMap* tm) { asm volatile("prefetch.tensormap [%0];" ::"l"(tm) : "memory"); }
__device__ __forceinline__ void fence_async_smem() { asm volatile("fence.proxy.async.shared::cta;" ::: "memory"); }
template <int ID, int N> __device__ __forceinline__ void bar_sync_c() { asm volatile("bar.sync %0, %1;" ::"n"(ID), "n"(N) : "memory"); }
__device__ __forceinline__ void wg_fence() { asm volatile("wgmma.fence.sync.aligned;" ::: "memory"); }
__device__ __forceinline__ void wg_commit() { asm volatile("wgmma.commit_group.sync.aligned;" ::: "memory"); }
template <int N> __device__ __forceinline__ void wg_wait() { asm volatile("wgmma.wait_group.sync.aligned %0;" ::"n"(N) : "memory"); }
template <int N> __device__ __forceinline__ void reg_fence(float (&d)[N]) {
#pragma unroll
  for (int i = 0; i < N; i++) asm volatile("" : "+f"(d[i])::"memory");
}
template <int N> __device__ __forceinline__ void reg_fence(uint32_t (&d)[N]) {
#pragma unroll
  for (int i = 0; i < N; i++) asm volatile("" : "+r"(d[i])::"memory");
}
__device__ __forceinline__ uint64_t mk_desc(uint32_t addr, uint32_t lbo, uint32_t sbo, uint32_t sw) {
  return (uint64_t)((addr & 0x3FFFF) >> 4) | ((uint64_t)(lbo >> 4) << 16) | ((uint64_t)(sbo >> 4) << 32) | ((uint64_t)sw << 62);
}
__device__ __forceinline__ uint32_t pack_bf16(float lo, float hi) {
  uint32_t r; asm("cvt.rn.bf16x2.f32 %0, %1, %2;" : "=r"(r) : "f"(hi), "f"(lo)); return r;
}
__device__ __forceinline__ uint32_t pack_relu(float lo, float hi) {
  uint32_t r; asm("cvt.rn.relu.bf16x2.f32 %0, %1, %2;" : "=r"(r) : "f"(hi), "f"(lo)); return r;
}
__device__ __forceinline__ float bf_lo(uint32_t u) { return __uint_as_float(u << 16); }
__device__ __forceinline__ float bf_hi(uint32_t u) { return __uint_as_float(u & 0xffff0000u); }
__device__ __forceinline__ float ex2(float x) { float r; asm("ex2.approx.ftz.f32 %0, %1;" : "=f"(r) : "f"(x)); return r; }
__device__ __forceinline__ float rcp(float x) { float r; asm("rcp.approx.ftz.f32 %0, %1;" : "=f"(r) : "f"(x)); return r; }
__device__ __forceinline__ void stsm4(uint32_t addr, uint32_t r0, uint32_t r1, uint32_t r2, uint32_t r3) {
  asm volatile("stmatrix.sync.aligned.m8n8.x4.shared.b16 [%0], {%1, %2, %3, %4};" ::"r"(addr), "r"(r0), "r"(r1), "r"(r2), "r"(r3) : "memory");
}
__device__ __forceinline__ uint4 lds128(uint32_t a) { uint4 v; asm volatile("ld.shared.v4.u32 {%0, %1, %2, %3}, [%4];" : "=r"(v.x), "=r"(v.y), "=r"(v.z), "=r"(v.w) : "r"(a) : "memory"); return v; }
__device__ __forceinline__ float2 lds64f(uint32_t a) { float2 v; asm volatile("ld.shared.v2.f32 {%0, %1}, [%2];" : "=f"(v.x), "=f"(v.y) : "r"(a) : "memory"); return v; }
__device__ __forceinline__ void sts128(uint32_t a, uint32_t x, uint32_t y, uint32_t z, uint32_t w) { asm volatile("st.shared.v4.u32 [%0], {%1, %2, %3, %4};" ::"r"(a), "r"(x), "r"(y), "r"(z), "r"(w) : "memory"); }
__device__ __forceinline__ void sts64f(uint32_t a, float x, float y) { asm volatile("st.shared.v2.f32 [%0], {%1, %2};" ::"r"(a), "f"(x), "f"(y) : "memory"); }
__device__ __forceinline__ void sts32(uint32_t a, uint32_t x) { asm volatile("st.shared.u32 [%0], %1;" ::"r"(a), "r"(x) : "memory"); }
__device__ __forceinline__ void sts16(uint32_t a, uint16_t x) { asm volatile("st.shared.u16 [%0], %1;" ::"r"(a), "h"(x) : "memory"); }

__device__ __forceinline__ void tma2d_mc(uint32_t dst, const CUtensorMap* tm, uint32_t bar, int c0, int c1) {
  asm volatile("cp.async.bulk.tensor.2d.shared::cluster.global.mbarrier::complete_tx::bytes.multicast::cluster [%0], [%1, {%3, %4}], [%2], %5;" ::"r"(dst), "l"(tm), "r"(bar), "r"(c0), "r"(c1), "h"((uint16_t)3) : "memory");
}
__device__ __forceinline__ void tma3d_mc(uint32_t dst, const CUtensorMap* tm, uint32_t bar, int c0, int c1, int c2) {
  asm volatile("cp.async.bulk.tensor.3d.shared::cluster.global.mbarrier::complete_tx::bytes.multicast::cluster [%0], [%1, {%3, %4, %5}], [%2], %6;" ::"r"(dst), "l"(tm), "r"(bar), "r"(c0), "r"(c1), "r"(c2), "h"((uint16_t)3) : "memory");
}
__device__ __forceinline__ void tma_prefetch2d(const CUtensorMap* tm, int c0, int c1) {
  asm volatile("cp.async.bulk.prefetch.tensor.2d.L2.global [%0, {%1, %2}];" ::"l"(tm), "r"(c0), "r"(c1) : "memory");
}
__device__ __forceinline__ void arrive_if(uint32_t bar, bool c) {
  asm volatile("{ .reg .pred p; setp.ne.u32 p, %1, 0; @p mbarrier.arrive.shared::cta.b64 _, [%0]; }" ::"r"(bar), "r"((uint32_t)c) : "memory");
}
__device__ __forceinline__ void arrive_pair(uint32_t bar, uint32_t lane) {
  asm volatile("{ .reg .pred p; .reg .b32 ra; setp.lt.u32 p, %1, 2; mapa.shared::cluster.u32 ra, %0, %2; @p mbarrier.arrive.shared::cluster.b64 _, [ra]; }" ::"r"(bar), "r"(lane), "r"(lane & 1) : "memory");
}
__device__ __forceinline__ void ldsm4(uint32_t addr, uint32_t& r0, uint32_t& r1, uint32_t& r2, uint32_t& r3) {
  asm volatile("ldmatrix.sync.aligned.m8n8.x4.shared.b16 {%0, %1, %2, %3}, [%4];" : "=r"(r0), "=r"(r1), "=r"(r2), "=r"(r3) : "r"(addr) : "memory");
}
__device__ __forceinline__ void st_unit(uint4* p, uint32_t x, uint32_t y, uint32_t z, uint32_t w) {
  asm volatile("st.relaxed.gpu.global.v4.b32 [%0], {%1, %2, %3, %4};" ::"l"(p), "r"(x), "r"(y), "r"(z), "r"(w) : "memory");
}
__device__ __forceinline__ void ld_unit(const uint4* p, uint32_t& x, uint32_t& y, uint32_t& z, uint32_t& w) {
  asm volatile("ld.relaxed.gpu.global.v4.b32 {%0, %1, %2, %3}, [%4];" : "=r"(x), "=r"(y), "=r"(z), "=r"(w) : "l"(p) : "memory");
}
__device__ __forceinline__ uint32_t ld_word(const uint32_t* p) { uint32_t v; asm volatile("ld.relaxed.gpu.global.u32 %0, [%1];" : "=r"(v) : "l"(p) : "memory"); return v; }
__device__ __forceinline__ void st_hint_if(uint32_t* p, uint32_t v, bool c) {
  asm volatile("{ .reg .pred p; setp.ne.u32 p, %2, 0; @p st.relaxed.gpu.global.u32 [%0], %1; }" ::"l"(p), "r"(v), "r"((uint32_t)c) : "memory");
}
__device__ __forceinline__ void st_hint(uint32_t* p, uint32_t v) { asm volatile("st.relaxed.gpu.global.u32 [%0], %1;" ::"l"(p), "r"(v) : "memory"); }
template <int LM> __device__ __forceinline__ void hint_wait(const uint32_t* p, uint32_t lane, uint32_t v, uint32_t mask) {
  uint32_t got;
  do {
    uint32_t x;
    asm volatile("ld.relaxed.gpu.global.u32 %0, [%1];" : "=r"(x) : "l"(p + (lane & LM)) : "memory");
    got = __ballot_sync(~0u, x == v);
  } while ((got & mask) != mask);
}
__device__ __forceinline__ uint32_t pack_tag(float lo, float hi, uint32_t tag16) {
  const uint32_t r = ((__float_as_uint(lo) - tag16 + 0x10000u) & 0xfffe0000u) + tag16;
  return __byte_perm(r, pack_bf16(lo, hi), 0x7632);
}
template <int N> __device__ __forceinline__ void ld_units(uint32_t* r, const uint4* p, int stride) {
#pragma unroll
  for (int u = 0; u < N; u++) ld_unit(p + u * stride, r[4 * u], r[4 * u + 1], r[4 * u + 2], r[4 * u + 3]);
}
template <int N> __device__ __forceinline__ void fix_units(uint32_t* r, const uint4* p, int stride, uint32_t tag) {
  while (true) {
    uint32_t bad = r[0] ^ tag;
#pragma unroll
    for (int u = 1; u < N; u++) asm("lop3.b32 %0, %0, %1, %2, 0xF6;" : "+r"(bad) : "r"(r[4 * u]), "r"(tag));
    if (!__any_sync(~0u, bad & 1)) break;
    ld_units<N>(r, p, stride);
  }
}

template <int TB> __device__ __forceinline__ void wgmma_rs_n48(float (&d)[24], uint32_t a0, uint32_t a1, uint32_t a2, uint32_t a3, uint64_t db, int scale_d) {
  asm volatile("{ .reg .pred p; setp.ne.b32 p, %29, 0;\n"
    "wgmma.mma_async.sync.aligned.m64n48k16.f32.bf16.bf16 {%0, %1, %2, %3, %4, %5, %6, %7, %8, %9, %10, %11, %12, %13, %14, %15, %16, %17, %18, %19, %20, %21, %22, %23}, {%24, %25, %26, %27}, %28, p, 1, 1, %30; }"
    : "+f"(d[0]), "+f"(d[1]), "+f"(d[2]), "+f"(d[3]), "+f"(d[4]), "+f"(d[5]), "+f"(d[6]), "+f"(d[7]), "+f"(d[8]), "+f"(d[9]), "+f"(d[10]), "+f"(d[11]), "+f"(d[12]), "+f"(d[13]), "+f"(d[14]), "+f"(d[15]), "+f"(d[16]), "+f"(d[17]), "+f"(d[18]), "+f"(d[19]), "+f"(d[20]), "+f"(d[21]), "+f"(d[22]), "+f"(d[23])
    : "r"(a0), "r"(a1), "r"(a2), "r"(a3), "l"(db), "r"(scale_d), "n"(TB));
}

template <int TB> __device__ __forceinline__ void wgmma_rs_n64(float (&d)[32], uint32_t a0, uint32_t a1, uint32_t a2, uint32_t a3, uint64_t db, int scale_d) {
  asm volatile("{ .reg .pred p; setp.ne.b32 p, %37, 0;\n"
    "wgmma.mma_async.sync.aligned.m64n64k16.f32.bf16.bf16 {%0, %1, %2, %3, %4, %5, %6, %7, %8, %9, %10, %11, %12, %13, %14, %15, %16, %17, %18, %19, %20, %21, %22, %23, %24, %25, %26, %27, %28, %29, %30, %31}, {%32, %33, %34, %35}, %36, p, 1, 1, %38; }"
    : "+f"(d[0]), "+f"(d[1]), "+f"(d[2]), "+f"(d[3]), "+f"(d[4]), "+f"(d[5]), "+f"(d[6]), "+f"(d[7]), "+f"(d[8]), "+f"(d[9]), "+f"(d[10]), "+f"(d[11]), "+f"(d[12]), "+f"(d[13]), "+f"(d[14]), "+f"(d[15]), "+f"(d[16]), "+f"(d[17]), "+f"(d[18]), "+f"(d[19]), "+f"(d[20]), "+f"(d[21]), "+f"(d[22]), "+f"(d[23]), "+f"(d[24]), "+f"(d[25]), "+f"(d[26]), "+f"(d[27]), "+f"(d[28]), "+f"(d[29]), "+f"(d[30]), "+f"(d[31])
    : "r"(a0), "r"(a1), "r"(a2), "r"(a3), "l"(db), "r"(scale_d), "n"(TB));
}

template <int TB> __device__ __forceinline__ void wgmma_rs_n80(float (&d)[40], uint32_t a0, uint32_t a1, uint32_t a2, uint32_t a3, uint64_t db, int scale_d) {
  asm volatile("{ .reg .pred p; setp.ne.b32 p, %45, 0;\n"
    "wgmma.mma_async.sync.aligned.m64n80k16.f32.bf16.bf16 {%0, %1, %2, %3, %4, %5, %6, %7, %8, %9, %10, %11, %12, %13, %14, %15, %16, %17, %18, %19, %20, %21, %22, %23, %24, %25, %26, %27, %28, %29, %30, %31, %32, %33, %34, %35, %36, %37, %38, %39}, {%40, %41, %42, %43}, %44, p, 1, 1, %46; }"
    : "+f"(d[0]), "+f"(d[1]), "+f"(d[2]), "+f"(d[3]), "+f"(d[4]), "+f"(d[5]), "+f"(d[6]), "+f"(d[7]), "+f"(d[8]), "+f"(d[9]), "+f"(d[10]), "+f"(d[11]), "+f"(d[12]), "+f"(d[13]), "+f"(d[14]), "+f"(d[15]), "+f"(d[16]), "+f"(d[17]), "+f"(d[18]), "+f"(d[19]), "+f"(d[20]), "+f"(d[21]), "+f"(d[22]), "+f"(d[23]), "+f"(d[24]), "+f"(d[25]), "+f"(d[26]), "+f"(d[27]), "+f"(d[28]), "+f"(d[29]), "+f"(d[30]), "+f"(d[31]), "+f"(d[32]), "+f"(d[33]), "+f"(d[34]), "+f"(d[35]), "+f"(d[36]), "+f"(d[37]), "+f"(d[38]), "+f"(d[39])
    : "r"(a0), "r"(a1), "r"(a2), "r"(a3), "l"(db), "r"(scale_d), "n"(TB));
}

template <int TB> __device__ __forceinline__ void wgmma_rs_n160(float (&d)[80], uint32_t a0, uint32_t a1, uint32_t a2, uint32_t a3, uint64_t db, int scale_d) {
  asm volatile("{ .reg .pred p; setp.ne.b32 p, %85, 0;\n"
    "wgmma.mma_async.sync.aligned.m64n160k16.f32.bf16.bf16 {%0, %1, %2, %3, %4, %5, %6, %7, %8, %9, %10, %11, %12, %13, %14, %15, %16, %17, %18, %19, %20, %21, %22, %23, %24, %25, %26, %27, %28, %29, %30, %31, %32, %33, %34, %35, %36, %37, %38, %39, %40, %41, %42, %43, %44, %45, %46, %47, %48, %49, %50, %51, %52, %53, %54, %55, %56, %57, %58, %59, %60, %61, %62, %63, %64, %65, %66, %67, %68, %69, %70, %71, %72, %73, %74, %75, %76, %77, %78, %79}, {%80, %81, %82, %83}, %84, p, 1, 1, %86; }"
    : "+f"(d[0]), "+f"(d[1]), "+f"(d[2]), "+f"(d[3]), "+f"(d[4]), "+f"(d[5]), "+f"(d[6]), "+f"(d[7]), "+f"(d[8]), "+f"(d[9]), "+f"(d[10]), "+f"(d[11]), "+f"(d[12]), "+f"(d[13]), "+f"(d[14]), "+f"(d[15]), "+f"(d[16]), "+f"(d[17]), "+f"(d[18]), "+f"(d[19]), "+f"(d[20]), "+f"(d[21]), "+f"(d[22]), "+f"(d[23]), "+f"(d[24]), "+f"(d[25]), "+f"(d[26]), "+f"(d[27]), "+f"(d[28]), "+f"(d[29]), "+f"(d[30]), "+f"(d[31]), "+f"(d[32]), "+f"(d[33]), "+f"(d[34]), "+f"(d[35]), "+f"(d[36]), "+f"(d[37]), "+f"(d[38]), "+f"(d[39]), "+f"(d[40]), "+f"(d[41]), "+f"(d[42]), "+f"(d[43]), "+f"(d[44]), "+f"(d[45]), "+f"(d[46]), "+f"(d[47]), "+f"(d[48]), "+f"(d[49]), "+f"(d[50]), "+f"(d[51]), "+f"(d[52]), "+f"(d[53]), "+f"(d[54]), "+f"(d[55]), "+f"(d[56]), "+f"(d[57]), "+f"(d[58]), "+f"(d[59]), "+f"(d[60]), "+f"(d[61]), "+f"(d[62]), "+f"(d[63]), "+f"(d[64]), "+f"(d[65]), "+f"(d[66]), "+f"(d[67]), "+f"(d[68]), "+f"(d[69]), "+f"(d[70]), "+f"(d[71]), "+f"(d[72]), "+f"(d[73]), "+f"(d[74]), "+f"(d[75]), "+f"(d[76]), "+f"(d[77]), "+f"(d[78]), "+f"(d[79])
    : "r"(a0), "r"(a1), "r"(a2), "r"(a3), "l"(db), "r"(scale_d), "n"(TB));
}

template <int TB> __device__ __forceinline__ void wgmma_rs_n192(float (&d)[96], uint32_t a0, uint32_t a1, uint32_t a2, uint32_t a3, uint64_t db, int scale_d) {
  asm volatile("{ .reg .pred p; setp.ne.b32 p, %101, 0;\n"
    "wgmma.mma_async.sync.aligned.m64n192k16.f32.bf16.bf16 {%0, %1, %2, %3, %4, %5, %6, %7, %8, %9, %10, %11, %12, %13, %14, %15, %16, %17, %18, %19, %20, %21, %22, %23, %24, %25, %26, %27, %28, %29, %30, %31, %32, %33, %34, %35, %36, %37, %38, %39, %40, %41, %42, %43, %44, %45, %46, %47, %48, %49, %50, %51, %52, %53, %54, %55, %56, %57, %58, %59, %60, %61, %62, %63, %64, %65, %66, %67, %68, %69, %70, %71, %72, %73, %74, %75, %76, %77, %78, %79, %80, %81, %82, %83, %84, %85, %86, %87, %88, %89, %90, %91, %92, %93, %94, %95}, {%96, %97, %98, %99}, %100, p, 1, 1, %102; }"
    : "+f"(d[0]), "+f"(d[1]), "+f"(d[2]), "+f"(d[3]), "+f"(d[4]), "+f"(d[5]), "+f"(d[6]), "+f"(d[7]), "+f"(d[8]), "+f"(d[9]), "+f"(d[10]), "+f"(d[11]), "+f"(d[12]), "+f"(d[13]), "+f"(d[14]), "+f"(d[15]), "+f"(d[16]), "+f"(d[17]), "+f"(d[18]), "+f"(d[19]), "+f"(d[20]), "+f"(d[21]), "+f"(d[22]), "+f"(d[23]), "+f"(d[24]), "+f"(d[25]), "+f"(d[26]), "+f"(d[27]), "+f"(d[28]), "+f"(d[29]), "+f"(d[30]), "+f"(d[31]), "+f"(d[32]), "+f"(d[33]), "+f"(d[34]), "+f"(d[35]), "+f"(d[36]), "+f"(d[37]), "+f"(d[38]), "+f"(d[39]), "+f"(d[40]), "+f"(d[41]), "+f"(d[42]), "+f"(d[43]), "+f"(d[44]), "+f"(d[45]), "+f"(d[46]), "+f"(d[47]), "+f"(d[48]), "+f"(d[49]), "+f"(d[50]), "+f"(d[51]), "+f"(d[52]), "+f"(d[53]), "+f"(d[54]), "+f"(d[55]), "+f"(d[56]), "+f"(d[57]), "+f"(d[58]), "+f"(d[59]), "+f"(d[60]), "+f"(d[61]), "+f"(d[62]), "+f"(d[63]), "+f"(d[64]), "+f"(d[65]), "+f"(d[66]), "+f"(d[67]), "+f"(d[68]), "+f"(d[69]), "+f"(d[70]), "+f"(d[71]), "+f"(d[72]), "+f"(d[73]), "+f"(d[74]), "+f"(d[75]), "+f"(d[76]), "+f"(d[77]), "+f"(d[78]), "+f"(d[79]), "+f"(d[80]), "+f"(d[81]), "+f"(d[82]), "+f"(d[83]), "+f"(d[84]), "+f"(d[85]), "+f"(d[86]), "+f"(d[87]), "+f"(d[88]), "+f"(d[89]), "+f"(d[90]), "+f"(d[91]), "+f"(d[92]), "+f"(d[93]), "+f"(d[94]), "+f"(d[95])
    : "r"(a0), "r"(a1), "r"(a2), "r"(a3), "l"(db), "r"(scale_d), "n"(TB));
}

template <int TB> __device__ __forceinline__ void wgmma_rs_n224(float (&d)[112], uint32_t a0, uint32_t a1, uint32_t a2, uint32_t a3, uint64_t db, int scale_d) {
  asm volatile("{ .reg .pred p; setp.ne.b32 p, %117, 0;\n"
    "wgmma.mma_async.sync.aligned.m64n224k16.f32.bf16.bf16 {%0, %1, %2, %3, %4, %5, %6, %7, %8, %9, %10, %11, %12, %13, %14, %15, %16, %17, %18, %19, %20, %21, %22, %23, %24, %25, %26, %27, %28, %29, %30, %31, %32, %33, %34, %35, %36, %37, %38, %39, %40, %41, %42, %43, %44, %45, %46, %47, %48, %49, %50, %51, %52, %53, %54, %55, %56, %57, %58, %59, %60, %61, %62, %63, %64, %65, %66, %67, %68, %69, %70, %71, %72, %73, %74, %75, %76, %77, %78, %79, %80, %81, %82, %83, %84, %85, %86, %87, %88, %89, %90, %91, %92, %93, %94, %95, %96, %97, %98, %99, %100, %101, %102, %103, %104, %105, %106, %107, %108, %109, %110, %111}, {%112, %113, %114, %115}, %116, p, 1, 1, %118; }"
    : "+f"(d[0]), "+f"(d[1]), "+f"(d[2]), "+f"(d[3]), "+f"(d[4]), "+f"(d[5]), "+f"(d[6]), "+f"(d[7]), "+f"(d[8]), "+f"(d[9]), "+f"(d[10]), "+f"(d[11]), "+f"(d[12]), "+f"(d[13]), "+f"(d[14]), "+f"(d[15]), "+f"(d[16]), "+f"(d[17]), "+f"(d[18]), "+f"(d[19]), "+f"(d[20]), "+f"(d[21]), "+f"(d[22]), "+f"(d[23]), "+f"(d[24]), "+f"(d[25]), "+f"(d[26]), "+f"(d[27]), "+f"(d[28]), "+f"(d[29]), "+f"(d[30]), "+f"(d[31]), "+f"(d[32]), "+f"(d[33]), "+f"(d[34]), "+f"(d[35]), "+f"(d[36]), "+f"(d[37]), "+f"(d[38]), "+f"(d[39]), "+f"(d[40]), "+f"(d[41]), "+f"(d[42]), "+f"(d[43]), "+f"(d[44]), "+f"(d[45]), "+f"(d[46]), "+f"(d[47]), "+f"(d[48]), "+f"(d[49]), "+f"(d[50]), "+f"(d[51]), "+f"(d[52]), "+f"(d[53]), "+f"(d[54]), "+f"(d[55]), "+f"(d[56]), "+f"(d[57]), "+f"(d[58]), "+f"(d[59]), "+f"(d[60]), "+f"(d[61]), "+f"(d[62]), "+f"(d[63]), "+f"(d[64]), "+f"(d[65]), "+f"(d[66]), "+f"(d[67]), "+f"(d[68]), "+f"(d[69]), "+f"(d[70]), "+f"(d[71]), "+f"(d[72]), "+f"(d[73]), "+f"(d[74]), "+f"(d[75]), "+f"(d[76]), "+f"(d[77]), "+f"(d[78]), "+f"(d[79]), "+f"(d[80]), "+f"(d[81]), "+f"(d[82]), "+f"(d[83]), "+f"(d[84]), "+f"(d[85]), "+f"(d[86]), "+f"(d[87]), "+f"(d[88]), "+f"(d[89]), "+f"(d[90]), "+f"(d[91]), "+f"(d[92]), "+f"(d[93]), "+f"(d[94]), "+f"(d[95]), "+f"(d[96]), "+f"(d[97]), "+f"(d[98]), "+f"(d[99]), "+f"(d[100]), "+f"(d[101]), "+f"(d[102]), "+f"(d[103]), "+f"(d[104]), "+f"(d[105]), "+f"(d[106]), "+f"(d[107]), "+f"(d[108]), "+f"(d[109]), "+f"(d[110]), "+f"(d[111])
    : "r"(a0), "r"(a1), "r"(a2), "r"(a3), "l"(db), "r"(scale_d), "n"(TB));
}

template <int TA, int TB> __device__ __forceinline__ void wgmma_ss_n80(float (&d)[40], uint64_t da, uint64_t db, int scale_d) {
  asm volatile("{ .reg .pred p; setp.ne.b32 p, %42, 0;\n"
    "wgmma.mma_async.sync.aligned.m64n80k16.f32.bf16.bf16 {%0, %1, %2, %3, %4, %5, %6, %7, %8, %9, %10, %11, %12, %13, %14, %15, %16, %17, %18, %19, %20, %21, %22, %23, %24, %25, %26, %27, %28, %29, %30, %31, %32, %33, %34, %35, %36, %37, %38, %39}, %40, %41, p, 1, 1, %43, %44; }"
    : "+f"(d[0]), "+f"(d[1]), "+f"(d[2]), "+f"(d[3]), "+f"(d[4]), "+f"(d[5]), "+f"(d[6]), "+f"(d[7]), "+f"(d[8]), "+f"(d[9]), "+f"(d[10]), "+f"(d[11]), "+f"(d[12]), "+f"(d[13]), "+f"(d[14]), "+f"(d[15]), "+f"(d[16]), "+f"(d[17]), "+f"(d[18]), "+f"(d[19]), "+f"(d[20]), "+f"(d[21]), "+f"(d[22]), "+f"(d[23]), "+f"(d[24]), "+f"(d[25]), "+f"(d[26]), "+f"(d[27]), "+f"(d[28]), "+f"(d[29]), "+f"(d[30]), "+f"(d[31]), "+f"(d[32]), "+f"(d[33]), "+f"(d[34]), "+f"(d[35]), "+f"(d[36]), "+f"(d[37]), "+f"(d[38]), "+f"(d[39])
    : "l"(da), "l"(db), "r"(scale_d), "n"(TA), "n"(TB));
}

struct RowStat { float sh, s, q; };
__device__ __forceinline__ void stat_word(RowStat& st, uint32_t u) {
  const float a = bf_lo(u) - st.sh, b = bf_hi(u) - st.sh;
  st.s += a + b; st.q = fmaf(a, a, st.q); st.q = fmaf(b, b, st.q);
}
__device__ __forceinline__ void stat_frags(RowStat& s0, RowStat& s1, const uint32_t (&a)[16], bool first) {
  if (first) { s0.sh = bf_lo(a[0]); s1.sh = bf_lo(a[1]); }
#pragma unroll
  for (int i = 0; i < 16; i += 2) { stat_word(s0, a[i]); stat_word(s1, a[i + 1]); }
}
__device__ __forceinline__ void stat_finish(const RowStat& st, float& mean, float& rstd) {
  float m = st.sh + st.s * (1.f / 160.f), m2 = fmaxf(st.q - st.s * st.s * (1.f / 160.f), 0.f);
  float mo = __shfl_xor_sync(~0u, m, 1), m2o = __shfl_xor_sync(~0u, m2, 1), dl = mo - m;
  m2 = m2 + m2o + dl * dl * 80.f; m = 0.5f * (m + mo);
  mo = __shfl_xor_sync(~0u, m, 2); m2o = __shfl_xor_sync(~0u, m2, 2); dl = mo - m;
  m2 = m2 + m2o + dl * dl * 160.f; mean = 0.5f * (m + mo);
  rstd = rsqrtf(m2 * (1.f / 640.f) + 1e-5f);
}

__device__ __forceinline__ float quad_sum(float v) { v += __shfl_xor_sync(~0u, v, 1); return v + __shfl_xor_sync(~0u, v, 2); }
__device__ __forceinline__ void feature_map(const float (&p)[40], float sc0, float sc1, uint32_t (&ep)[20], uint32_t (&em)[20]) {
#pragma unroll
  for (int hp = 0; hp < 2; hp++) {
#pragma unroll
    for (int r = 0; r < 2; r++) {
      const float sc = r ? sc1 : sc0;
      const int o = 20 * hp + 2 * r;
      float mx = fmaxf(fmaxf(fmaxf(p[o], p[o + 1]), fmaxf(p[o + 4], p[o + 5])), fmaxf(fmaxf(p[o + 8], p[o + 9]), fmaxf(p[o + 12], p[o + 13])));
      float mn = fminf(fminf(fminf(p[o], p[o + 1]), fminf(p[o + 4], p[o + 5])), fminf(fminf(p[o + 8], p[o + 9]), fminf(p[o + 12], p[o + 13])));
      mx = fmaxf(mx, fmaxf(p[o + 16], p[o + 17])); mn = fminf(mn, fminf(p[o + 16], p[o + 17]));
      mx = fmaxf(mx, __shfl_xor_sync(~0u, mx, 1)); mn = fminf(mn, __shfl_xor_sync(~0u, mn, 1));
      const float c = -mx * sc, d = mn * sc;
      float e[10], f[10];
#pragma unroll
      for (int k = 0; k < 10; k++) {
        const float x = p[o + 4 * (k >> 1) + (k & 1)];
        e[k] = ex2(fmaf(x, sc, c));
        f[k] = ex2(fmaf(x, -sc, d));
      }
      const float se = ((e[0] + e[1]) + (e[2] + e[3])) + ((e[4] + e[5]) + (e[6] + e[7])) + (e[8] + e[9]);
      const float sf = ((f[0] + f[1]) + (f[2] + f[3])) + ((f[4] + f[5]) + (f[6] + f[7])) + (f[8] + f[9]);
      const float re = rcp(se + __shfl_xor_sync(~0u, se, 1)), rf = rcp(sf + __shfl_xor_sync(~0u, sf, 1));
#pragma unroll
      for (int k = 0; k < 5; k++) {
        ep[2 * (5 * hp + k) + r] = pack_bf16(e[2 * k] * re, e[2 * k + 1] * re);
        em[2 * (5 * hp + k) + r] = pack_bf16(f[2 * k] * rf, f[2 * k + 1] * rf);
      }
    }
  }
}

__device__ __forceinline__ uint32_t wo_off(int kb) { return (kb < 5 ? 80 + 20 * kb : kb < 9 ? 20 * (kb - 5) : 180) * KB; }
__device__ __forceinline__ uint32_t ff_off(int p) { return ((0x521043u >> (4 * (p % 6))) & 15) * 32 * KB; }
__device__ __forceinline__ int f2_chunk(int s, int fp, int rank) { return (s < 2 ? 8 : ((fp + (s >> 1)) & 3) * 2) + ((s & 1) ? rank : rank ^ 1); }
__device__ __forceinline__ uint32_t f2_off(int s) { return ((0x4352u >> (4 * (s & 3))) & 15) * 32 * KB; }

#define ROLE_A()                                                                                      \
  uint32_t ca_;                                                                                       \
  asm volatile("ld.shared.u32 %0, [%1];" : "=r"(ca_) : "r"(BAR(B_COUNT) + 4) : "memory");             \
  const int bi = (ca_ >> 4) * 2 + (ca_ & 1), bj = (ca_ >> 1) & 7

template <bool BY_SM>
__global__ void __launch_bounds__(384, 1) fused_block_kernel(const __grid_constant__ Params P) {
  extern __shared__ __align__(1024) uint8_t smem_raw[];
  const uint32_t sb = (uint32_t)__cvta_generic_to_shared(smem_raw);
  const uint32_t bars = sb + OFF_BAR;
  auto BAR = [&](int id) { return bars + id * 8; };
  int tid; asm volatile("mov.u32 %0, %%tid.x;" : "=r"(tid));
  const int lane = tid & 31, warp = __shfl_sync(~0u, tid >> 5, 0);
  const int rank = blockIdx.x & 1;
  int role = blockIdx.x >> 1;
  if (BY_SM) {
    uint32_t smid; asm("mov.u32 %0, %%smid;" : "=r"(smid));
    const int tp = smid >> 1;
    const int gp = tp < 32 ? (tp & 7) : tp < 60 ? 1 + (tp - 32) % 7 : 0;
    const int ix = tp < 32 ? (tp >> 3) : tp < 60 ? 4 + (tp - 32) / 7 : tp - 56 - SPARE;
    const int blk = gp == 0 ? 7 : gp == 6 ? 6 : gp == 7 ? 5 : gp - 1;
    if (tp >= 64 + SPARE || (tp >= 60 && tp < 60 + SPARE)) return;
    role = ((blk >> 1) * 2 + (ix & 1)) * 8 + (blk & 1) * 4 + (ix >> 1);
  }
  const int cta = role * 2 + rank;
  const int bi = (role >> 3) * 2 + rank;
  const int bj = role & 7;
  const int fi = (role >> 4) * 4 + (role & 3);
  const int fp = ((role >> 2) & 1) * 2 + ((role >> 3) & 1);
  const int fj = fp * 2 + rank;
  const bool wide = fj < 6;
  const int ffc0 = wide ? 224 * fj : 1344 + 192 * (fj - 6);
  const int ffm = ffc0 + ((wide && rank) ? 32 : 0), ffh = wide ? (rank ? ffc0 : ffc0 + 192) : ffc0;

  if ((sb & 1023) != 0) return;
  auto load_a = [&](int kb) {
    const uint32_t st = sb + (kb & 3) * 48 * KB, fb = BAR(B_FA + kb);
    mbar_expect(fb, 16384 + 24576 + 6144);
    tma2d(st, &P.x, fb, kb * 64, bi * 128);
  };
  if (lane == 0) {
    if (warp == 8) {
#pragma unroll
      for (int i = 0; i < 10; i++) mbar_init(BAR(B_FA + i), 1);
      fence_async_smem();
      load_a(0);
#pragma unroll 1
      for (int h = 0; h < 2; h++) {
        tma3d(sb + 16 * KB + h * 12 * KB, &P.wqkv_main, BAR(B_FA), bj * 80, h * 32, 0);
        tma3d(sb + 40 * KB + h * 3 * KB, &P.wqkv_tail, BAR(B_FA), bj * 80 + 64, h * 32, 0);
      }
      load_a(1);
    } else if (warp > 0 && warp < 7) {
      const uint32_t b0 = BAR(warp * 10), c = warp < 4 ? 1 : 16;
#pragma unroll
      for (int i = 0; i < 10; i++) mbar_init(b0 + i * 8, c);
    } else if (warp == 7) {
#pragma unroll
      for (int i = 0; i < 10; i++) { mbar_init(BAR(B_DS + i), 1); mbar_expect(BAR(B_DS + i), 8192); }
    } else if (warp == 0) {
#pragma unroll
      for (int i = 0; i < 7; i++) mbar_init(BAR(B_EG + i), 8);
      mbar_init(BAR(B_FX), 1); mbar_init(BAR(B_CS), 2); mbar_init(BAR(B_DONE), 8 + 3); mbar_init(BAR(B_KVZ), 3); mbar_init(BAR(B_HZ), 3);
      sts32(BAR(B_COUNT), role); sts32(BAR(B_COUNT) + 4, cta);
    }
    asm volatile("fence.mbarrier_init.release.cluster;" ::: "memory");
  }
  fence_async_smem();
  __syncthreads();
  asm volatile("barrier.cluster.arrive.relaxed.aligned;" ::: "memory");

  if (warp >= 8) {
    asm volatile("setmaxnreg.dec.sync.aligned.u32 %0;" ::"n"(HREG));
    if (warp == 8) {
      asm volatile("barrier.cluster.wait.aligned;" ::: "memory");
      if (lane == 0) {
        TSTAMP(21);
        {
          uint32_t other;
          asm volatile("{ .reg .b32 ra; mapa.shared::cluster.u32 ra, %1, %2; ld.shared::cluster.u32 %0, [ra]; }" : "=r"(other) : "r"(BAR(B_COUNT)), "r"(rank ^ 1) : "memory");
          if (other != (uint32_t)role) asm volatile("trap;");
        }
#pragma unroll 1
        for (int kb = 1; kb < 10; kb++) {
          const uint32_t st = sb + (kb & 3) * 48 * KB, fb = BAR(B_FA + kb);
          if (kb >= 4) mbar_wait_bounded(BAR(B_EA + kb - 4));
          if (kb >= 2) load_a(kb);
          tma3d_mc(st + 16 * KB + rank * 12 * KB, &P.wqkv_main, fb, bj * 80, kb * 64 + rank * 32, 0);
          tma3d_mc(st + 40 * KB + rank * 3 * KB, &P.wqkv_tail, fb, bj * 80 + 64, kb * 64 + rank * 32, 0);
          if (kb == 3) {
            if (bj < 6) tma_prefetch2d(&P.x, (4 + bj) * 64, bi * 128);
            l2_prefetch((const uint8_t*)P.pwqkv + 256 * 3840 + cta * 11520, 11520);
            prefetch_tmap(&P.wo); prefetch_tmap(&P.xt); prefetch_tmap(&P.w1_main); prefetch_tmap(&P.w1_half); prefetch_tmap(&P.w2_main); prefetch_tmap(&P.w2_half); prefetch_tmap(&P.out_st);
          }
          if (kb == PF_KB) l2_prefetch((const uint8_t*)P.pwo + cta * 6400, 6400);
          if (kb == PF_KB + 1) l2_prefetch((const uint8_t*)P.pw1 + cta * 17280, 17280);
          if (kb == PF_KB + 2) l2_prefetch((const uint8_t*)P.pw2 + cta * 17280, 17280);
        }
        auto wo_b = [&](int kb) {
          mbar_expect(BAR(B_FW + kb), 20480);
          tma3d_mc(sb + wo_off(kb) + rank * 10 * KB, &P.wo, BAR(B_FW + kb), 0, kb * 64 + rank * 32, 5 * (bj & 3));
        };
#pragma unroll 1
        for (int q = 0; q < 10; q++) {
          const int kb = (int)((0x9876504321ull >> (4 * q)) & 15);
          if (q == 0) mbar_wait_bounded(BAR(B_EA + 6));
          if (q == 2) mbar_wait_bounded(BAR(B_EA + 7));
          if (q == 4) mbar_wait_bounded(BAR(B_EA + 9));
          if (q == 5) mbar_wait_bounded(BAR(B_KVFREE));
          if (q >= 5 + W_FL) mbar_wait_bounded(BAR(B_FW + kb - W_FL));
          wo_b(kb);
        }
        mbar_wait_bounded(BAR(B_EW + 0));
        mbar_expect(BAR(B_FX), 20480);
        tma3d(sb + OFF_XT, &P.xt, BAR(B_FX), 0, bi * 128 + (bj >> 2) * 64, 5 * (bj & 3));
#pragma unroll 1
        for (int kb = 0; kb < 10; kb++) {
          mbar_wait_bounded(kb < 6 ? BAR(B_EW + ((0x333211 >> (4 * kb)) & 15)) : BAR(B_EF + kb - 6));
          if (kb == 3) mbar_wait_bounded(BAR(B_HGO));
          const uint32_t st = sb + ff_off(kb), fb = BAR(B_FF + kb);
          mbar_expect(fb, 24576 + (wide ? 4096 : 0));
#pragma unroll 1
          for (int h = 0; h < 2; h++) {
            tma3d(st + h * 16 * KB, &P.w1_main, fb, ffm, kb * 64 + h * 32, 0);
            if (wide) tma2d(st + h * 16 * KB + 12 * KB, &P.w1_half, fb, ffh, kb * 64 + h * 32);
          }
        }
#pragma unroll 1
        for (int s = 0; s < 10; s++) {
          mbar_wait_bounded(s < 4 ? BAR(B_EF + 4 + s) : BAR(B_EG + s - 4));
          const uint32_t st = sb + f2_off(s), fb = BAR(B_FG + s);
          const int col = f2_chunk(s, fp, rank) * 64;
          mbar_expect(fb, 28672);
          tma2d(st, &P.w2_main, fb, col, ffm);
          tma2d(st + 24 * KB, &P.w2_half, fb, col, ffh);
        }
        TSTAMP(35);
        mbar_arrive(BAR(B_DONE));
      }
    } else {
      const int ht = tid - 288, hw = warp - 9;
      const uint32_t e1 = ld_word(a_epoch(P.arena) + cta) + 1, tag = e1 & 1, tag16 = tag << 16;
      {
        uint2 w[5];
        const int k = ht < 80 ? ht : 79, h = k / 20;
#pragma unroll
        for (int q = 0; q < 5; q++) w[q] = __ldg((const uint2*)(P.pwphi + bj * 1600 + k * 20) + q);
#pragma unroll 1
        for (int i = ht; i < 800; i += 96) sts128(sb + OFF_WPHI + i * 16, 0, 0, 0, 0);
        bar_sync_c<4, 96>();
        const uint32_t base = sb + OFF_WPHI + (h >> 1) * 6400 + (k >> 3) * 128 + (k & 7) * 16 + (h & 1) * 8;
#pragma unroll
        for (int fp = 0; fp < 10; fp++) sts32(base + (fp % 5) * 1280 + (fp / 5) * 4, (fp & 1) ? w[fp >> 1].y : w[fp >> 1].x);
        fence_async_smem();
      }
      {
        const uint32_t tmp = sb + OFF_KVB;
        mbar_wait(BAR(B_FA + CS_KB));
        if (lane < 30) {
          const int grp = hw * 2 + lane / 15, oct = rank * 15 + lane % 15, nr = grp < 2 ? 14 : 13;
          const __nv_bfloat16* src = P.pwqkv + (size_t)((bi >> 1) * 80 + grp * 13 + (grp < 2 ? grp : 2)) * 1920 + (oct / 10) * 640 + bj * 80 + (oct % 10) * 8;
          float a[8] = {0, 0, 0, 0, 0, 0, 0, 0};
#pragma unroll 1
          for (int r = 0; r < 14; r += 7) {
            uint4 u[7];
#pragma unroll
            for (int k = 0; k < 7; k++) u[k] = (r + k < nr) ? __ldg((const uint4*)(src + (r + k) * 1920)) : make_uint4(0, 0, 0, 0);
#pragma unroll
            for (int k = 0; k < 7; k++) {
              a[0] += bf_lo(u[k].x); a[1] += bf_hi(u[k].x); a[2] += bf_lo(u[k].y); a[3] += bf_hi(u[k].y);
              a[4] += bf_lo(u[k].z); a[5] += bf_hi(u[k].z); a[6] += bf_lo(u[k].w); a[7] += bf_hi(u[k].w);
            }
          }
          sts128(tmp + hw * 960 + lane * 32, __float_as_uint(a[0]), __float_as_uint(a[1]), __float_as_uint(a[2]), __float_as_uint(a[3]));
          sts128(tmp + hw * 960 + lane * 32 + 16, __float_as_uint(a[4]), __float_as_uint(a[5]), __float_as_uint(a[6]), __float_as_uint(a[7]));
        }
        bar_sync_c<4, 96>();
        if (hw < 2) {
          if (ht < 30) {
            float a[4] = {0, 0, 0, 0};
#pragma unroll
            for (int k = 0; k < 6; k++) {
              const uint4 p = lds128(tmp + k * 480 + ht * 16);
              a[0] += __uint_as_float(p.x); a[1] += __uint_as_float(p.y); a[2] += __uint_as_float(p.z); a[3] += __uint_as_float(p.w);
            }
            st_unit(a_csp(P.arena) + (bj * 8 + (bi >> 1)) * 60 + rank * 30 + ht, (__float_as_uint(a[0]) & ~1u) | tag, __float_as_uint(a[1]), __float_as_uint(a[2]), __float_as_uint(a[3]));
          }
          if (ht == 0) TSTAMP(23);
          mbar_wait(BAR(B_FA + 7));
          const uint4* slot = a_csp(P.arena) + bj * 8 * 60 + (ht < 60 ? ht : 0);
          uint32_t u[32];
          while (true) {
            ld_units<8>(u, slot, 60);
            uint32_t bad = 0;
#pragma unroll
            for (int k = 0; k < 8; k++) bad |= u[4 * k] ^ tag;
            if (!__any_sync(~0u, bad & 1)) break;
            __nanosleep(200);
          }
          float a[4] = {0, 0, 0, 0};
#pragma unroll
          for (int k = 0; k < 32; k++) a[k & 3] += __uint_as_float(u[k]);
          if (ht < 60) sts128(sb + OFF_CS + ht * 16, __float_as_uint(a[0]), __float_as_uint(a[1]), __float_as_uint(a[2]), __float_as_uint(a[3]));
          if (ht == 63) sts32(BAR(B_COUNT) + 8, e1);
          __syncwarp();
          if (lane == 0) mbar_arrive(BAR(B_CS));
          if (ht == 0) TSTAMP(36);
        }
      }
      asm volatile("barrier.cluster.wait.aligned;" ::: "memory");
      bar_sync_c<4, 96>();
#pragma unroll 1
      for (int i = ht; i < 1152; i += 96) sts128(sb + OFF_KVB + i * 16, 0, 0, 0, 0);
#pragma unroll 1
      for (int i = hw; i < 16; i += 3) st_unit(a_kvp(P.arena) + ((bj * 16 + i) * 16 + bi) * 32 + lane, tag ^ 1, 0, 0, 0);
      if (ht < 32) st_unit(a_kvf(P.arena) + bj * 512 + bi * 32 + ht, tag ^ 1, 0, 0, 0);
      else if (ht < 40) st_hint(a_hint_o(P.arena, bi) + ((ht - 32) * 8 + bj) * OHS, 0);
      __syncwarp();
      if (lane == 0) mbar_arrive(BAR(B_KVZ));
      auto reset_oh = [&]() {
        if (ORS) {
#pragma unroll 1
          for (int i = hw; i < 40; i += 3) st_unit(a_of(P.arena, bi) + ((i / 5) * 40 + bj * 5 + i % 5) * 32 + lane, tag ^ 1, 0, 0, 0);
        }
#pragma unroll 1
        for (int i = hw; i < 40; i += 3) st_unit(a_hf(P.arena, bi) + (((bj >> 2) * 4 + i / 10) * 40 + (bj & 3) * 10 + i % 10) * 32 + lane, tag ^ 1, 0, 0, 0);
        if (ht < 64) st_unit(a_hst(P.arena, bi) + (((bj >> 2) * 4 + (ht >> 4)) * 8 + (bj & 3) * 2) * 8 + (ht & 15), tag ^ 1, 0, 0, 0);
        __syncwarp();
        if (lane == 0) mbar_arrive(BAR(B_HZ));
      };
      if (HRS == 0) mbar_wait(BAR(B_FA + 9));
      if (HRS < 2) reset_oh();
      {
        mbar_wait(BAR(B_KVST));
        if (ht == 0) TSTAMP(38);
        const int un = hw * 16 + (lane & 15);
        const bool ok = hw < 2 && bi * 32 + un < 504;
        const uint4* pp = a_kvp(P.arena) + ((bj * 16 + bi) * 16 + (lane >> 4) * 8) * 32 + (ok ? un : 0);
        uint32_t u[32];
        ld_units<8>(u, pp, 32);
        fix_units<8>(u, pp, 32, tag);
        float v[8];
#pragma unroll
        for (int k = 0; k < 4; k++) {
          v[2 * k] = bf_lo(u[k]); v[2 * k + 1] = bf_hi(u[k]);
#pragma unroll
          for (int q = 1; q < 8; q++) { v[2 * k] += bf_lo(u[4 * q + k]); v[2 * k + 1] += bf_hi(u[4 * q + k]); }
        }
#pragma unroll
        for (int k = 0; k < 8; k++) v[k] += __shfl_xor_sync(~0u, v[k], 16);
        if (lane < 16 && ok) st_unit(a_kvf(P.arena) + bj * 512 + bi * 32 + un, pack_tag(v[0], v[1], tag16), pack_bf16(v[2], v[3]), pack_bf16(v[4], v[5]), pack_bf16(v[6], v[7]));
        if (ht == 0) TSTAMP(39);
      }
      if (HRS == 2) reset_oh();
      if (hw == 2) {
        if (lane == 0) watchdog(BAR(B_DONE));
      } else {
        const int ch = 8 + (fj >> 2), swg = (fj >> 1) & 1, sw = (fj & 1) * 2 + hw;
        mbar_wait(BAR(B_EG + 3));
        hint_wait<3>(a_hint_p(P.arena, fi) + (ch * 8 + swg * 4 + sw) * 8, lane, e1, 0xf);
        float c[32];
        uint32_t u[16];
        {
#pragma unroll
          for (int i = 0; i < 32; i++) c[i] = 0.f;
        }
#pragma unroll 1
        for (int sj = 0; sj < 4; sj++) {
          const uint4* pp = a_part(P.arena, fi) + (((ch * 4 + sj) * 2 + swg) * 4) * 128 + sw * 32 + lane;
          ld_units<4>(u, pp, 128);
          fix_units<4>(u, pp, 128, tag);
#pragma unroll
          for (int i = 0; i < 16; i++) { c[2 * i] += bf_lo(u[i]); c[2 * i + 1] += bf_hi(u[i]); }
        }
        {
          ld_units<4>(u, a_hf(P.arena, fi) + ((swg * 4 + sw) * 40 + ch * 4) * 32 + lane, 32);
          mbar_wait(BAR(B_EG));
          const float2 rs = lds64f(sb + OFF_CS + ((swg * 4 + sw) * 8 + (lane >> 2)) * 8);
#pragma unroll
          for (int i = 0; i < 16; i++) {
            c[2 * i] = fmaf(c[2 * i], (i & 1) ? rs.y : rs.x, bf_lo(u[i])); c[2 * i + 1] = fmaf(c[2 * i + 1], (i & 1) ? rs.y : rs.x, bf_hi(u[i]));
          }
        }
        const uint32_t sa = sb + OFF_STG + (12 + hw) * 2048;
#pragma unroll
        for (int n = 0; n < 8; n += 2)
          stsm4(sa + (lane & 15) * 128 + (((n + (lane >> 4)) ^ (lane & 7)) << 4), pack_bf16(c[4 * n], c[4 * n + 1]), pack_bf16(c[4 * n + 2], c[4 * n + 3]),
                pack_bf16(c[4 * n + 4], c[4 * n + 5]), pack_bf16(c[4 * n + 6], c[4 * n + 7]));
        fence_async_smem();
        __syncwarp();
        if (lane == 0) {
          tma_store2d(&P.out_st, sa, ch * 64, fi * 128 + swg * 64 + sw * 16);
          bulk_commit(); bulk_wait0();
          mbar_arrive(BAR(B_DONE));
        }
      }
    }
  } else {
    asm volatile("setmaxnreg.inc.sync.aligned.u32 %0;" ::"n"(CREG));
    const int wg = warp >> 2, wq = warp & 3;
    const int g = lane >> 2, t = lane & 3;
    const bool lowt = t < 2;
    const int smRow = wg * 64 + wq * 16 + (lane & 15);
    const int smOct = lane >> 4;
    if (tid == 0) TSTAMP(0);

    asm volatile("barrier.cluster.wait.aligned;" ::: "memory");
    uint32_t e1;
    float mean0, rstd0, mean1, rstd1;
    uint32_t fq_p[20], fq_m[20], tag, tag16;
    {
      float am[96], at[24];
      RowStat st0 = {0.f, 0.f, 0.f}, st1 = {0.f, 0.f, 0.f};
      uint32_t xa[16], xb[16];
      reg_fence(am); reg_fence(at);
      if (tid == 0) TSTAMP(22);
      auto stepA = [&](uint32_t (&x)[16], int kb) {
        const uint32_t s0 = sb + (kb & 3) * 48 * KB;
        mbar_wait(BAR(B_FA + kb));
        if (tid == 0) TSTAMP2(40 + kb);
#pragma unroll
        for (int kk = 0; kk < 4; kk++) ldsm4(s0 + smRow * 128 + (((2 * kk + smOct) ^ (lane & 7)) << 4), x[4 * kk], x[4 * kk + 1], x[4 * kk + 2], x[4 * kk + 3]);
        stat_frags(st0, st1, x, kb == 0);
        const uint64_t dm = mk_desc(s0 + 16 * KB, 4 * KB, 1024, 1), dt = mk_desc(s0 + 40 * KB, KB, 256, 3);
        reg_fence(x);
        if (A_PP) asm volatile("bar.sync %0, 256;" ::"r"(2 + wg) : "memory");
        wg_fence();
#pragma unroll
        for (int kk = 0; kk < 4; kk++) {
          if (A_PP && kk == 3 && (kb < 9 || wg == 0)) asm volatile("bar.arrive %0, 256;" ::"r"(3 - wg) : "memory");
          wgmma_rs_n192<1>(am, x[4 * kk], x[4 * kk + 1], x[4 * kk + 2], x[4 * kk + 3], dm + (kk >> 1) * 768 + (kk & 1) * 128, kb | kk);
          wgmma_rs_n48<1>(at, x[4 * kk], x[4 * kk + 1], x[4 * kk + 2], x[4 * kk + 3], dt + (kk >> 1) * 192 + (kk & 1) * 32, kb | kk);
        }
        wg_commit();
        wg_wait<1>();
        if (kb > 0) arrive_pair(BAR(B_EA + kb - 1), lane);
      };
      if (A_PP && wg == 1) asm volatile("bar.arrive 2, 256;" ::: "memory");
#pragma unroll 1
      for (int kb = 0; kb < 10; kb += 2) { stepA(xa, kb); stepA(xb, kb + 1); }
      wg_wait<0>();
      reg_fence(am); reg_fence(at); reg_fence(xa); reg_fence(xb);
      arrive_pair(BAR(B_EA + 9), lane);
      ROLE_A();
#define AQ(i) ((i) < 32 ? am[(i)] : at[(i) - 32])
#define AK(i) ((i) < 32 ? am[32 + (i)] : at[(i) - 24])
#define AV(i) ((i) < 32 ? am[64 + (i)] : at[(i) - 16])
      if (tid == 0) TSTAMP(1);
      stat_finish(st0, mean0, rstd0); stat_finish(st1, mean1, rstd1);
      const float L2E = 1.4426950408889634f;
      const float sc0 = rstd0 * L2E, sc1 = rstd1 * L2E;
      mbar_wait(BAR(B_CS));
      asm volatile("ld.shared.u32 %0, [%1];" : "=r"(e1) : "r"(BAR(B_COUNT) + 8) : "memory");
      tag = e1 & 1; tag16 = tag << 16;
      if (tid == 0) TSTAMP(16);
      const uint64_t dphi = mk_desc(sb + OFF_WPHI, 128, 1280, 0);

      uint32_t fa[20];
#pragma unroll
      for (int n = 0; n < 10; n++) {
        const float2 c = lds64f(sb + OFF_CS + (80 + 8 * n + 2 * t) * 4);
        fa[2 * n] = pack_bf16(fmaf(-mean0, c.x, AK(4 * n)), fmaf(-mean0, c.y, AK(4 * n + 1)));
        fa[2 * n + 1] = pack_bf16(fmaf(-mean1, c.x, AK(4 * n + 2)), fmaf(-mean1, c.y, AK(4 * n + 3)));
      }
      float ak[40], aq[40];
      reg_fence(fa); reg_fence(ak);
      wg_fence();
#pragma unroll
      for (int ks = 0; ks < 5; ks++) wgmma_rs_n80<1>(ak, fa[4 * ks], fa[4 * ks + 1], fa[4 * ks + 2], fa[4 * ks + 3], dphi + ks * 16, ks);
      wg_commit();
      uint32_t fv[20];
      {
#pragma unroll
        for (int n = 0; n < 10; n++) {
          const float2 c = lds64f(sb + OFF_CS + (160 + 8 * n + 2 * t) * 4);
          fv[2 * n] = pack_bf16(fmaf(-mean0, c.x, AV(4 * n)) * rstd0, fmaf(-mean0, c.y, AV(4 * n + 1)) * rstd0);
          fv[2 * n + 1] = pack_bf16(fmaf(-mean1, c.x, AV(4 * n + 2)) * rstd1, fmaf(-mean1, c.y, AV(4 * n + 3)) * rstd1);
        }
      }
      wg_wait<0>();
      reg_fence(ak); reg_fence(fa);
      if (tid == 0) TSTAMP(17);
      {
        uint32_t ep[20], em[20];
        feature_map(ak, sc0, sc1, ep, em);
        mbar_wait(BAR(B_EA + 9));
#pragma unroll
        for (int n = 0; n < 10; n += 2) {
          const int oct = n + smOct, ch = oct >= 5;
          stsm4(sb + OFF_V + ch * 16 * KB + smRow * 128 + (((oct - 5 * ch) ^ (smRow & 7)) << 4), fv[2 * n], fv[2 * n + 1], fv[2 * n + 2], fv[2 * n + 3]);
        }
        sts128(sb + OFF_V + smOct * 16 * KB + smRow * 128 + ((5 ^ (smRow & 7)) << 4), 0x3f80u, 0, 0, 0);
#pragma unroll
        for (int n = 0; n < 10; n += 2) {
          const int oct = n + smOct, hf = oct >= 5, ol = oct - 5 * hf;
          const int tm = ol < 3 ? hf : 2, pm = ol < 3 ? 5 + ol : 2 * hf + ol - 3;
          stsm4(sb + OFF_PHIK + hf * 16 * KB + smRow * 128 + ((ol ^ (smRow & 7)) << 4), ep[2 * n], ep[2 * n + 1], ep[2 * n + 2], ep[2 * n + 3]);
          stsm4(sb + OFF_PHIK + tm * 16 * KB + smRow * 128 + ((pm ^ (smRow & 7)) << 4), em[2 * n], em[2 * n + 1], em[2 * n + 2], em[2 * n + 3]);
        }
      }
      fence_async_smem();
      bar_sync_c<1, 256>();
      if (tid == 0) TSTAMP(2);
      {
        float c0[40];
        reg_fence(c0);
        const uint64_t dv = mk_desc(sb + OFF_V + wg * 16 * KB, 16 * KB, 1024, 1);
        const uint64_t d0 = mk_desc(sb + OFF_PHIK + wg * 16 * KB, wg ? 16 * KB + 32 : 32 * KB, 1024, 1);
        wg_fence();
#pragma unroll
        for (int ks = 0; ks < 8; ks++) wgmma_ss_n80<1, 1>(c0, dv + ks * 128, d0 + ks * 128, ks);
        wg_commit();
#pragma unroll
        for (int n = 0; n < 10; n++) {
          const float2 c = lds64f(sb + OFF_CS + (8 * n + 2 * t) * 4);
          fa[2 * n] = pack_bf16(fmaf(-mean0, c.x, AQ(4 * n)), fmaf(-mean0, c.y, AQ(4 * n + 1)));
          fa[2 * n + 1] = pack_bf16(fmaf(-mean1, c.x, AQ(4 * n + 2)), fmaf(-mean1, c.y, AQ(4 * n + 3)));
        }
        if (tid == 0) TSTAMP(24);
        mbar_wait(BAR(B_KVZ));
        if (tid == 0) TSTAMP(25);
        wg_wait<0>();
        reg_fence(c0);
        if (tid == 0) TSTAMP(26);
#pragma unroll
        for (int r = 0; r < 2; r++) {
          const int d = wq * 16 + g + 8 * r;
          if (d == 40 || (d < 40 && (d >= 20) == !lowt)) {
            const int u0 = ((wg * 42 + d + (d == 40 ? t >> 1 : 0)) * 2 + (t & 1)) * 3;
#pragma unroll
            for (int q = 0; q < 3; q++) {
              const int o = 16 * q + 2 * r, u = u0 + q;
              st_unit(a_kvp(P.arena) + ((bj * 16 + (u >> 5)) * 16 + bi) * 32 + (u & 31), (pack_bf16(c0[o], c0[o + 1]) & ~1u) | tag, pack_bf16(c0[o + 4], c0[o + 5]),
                      q < 2 ? pack_bf16(c0[(o + 8) % 40], c0[(o + 9) % 40]) : 0u, q < 2 ? pack_bf16(c0[(o + 12) % 40], c0[(o + 13) % 40]) : 0u);
            }
          }
        }
        __syncwarp();
        if (lane == 0) mbar_arrive(BAR(B_KVST));
      }
      if (tid == 0) TSTAMP(3);
      reg_fence(fa); reg_fence(aq);
      wg_fence();
#pragma unroll
      for (int ks = 0; ks < 5; ks++) wgmma_rs_n80<1>(aq, fa[4 * ks], fa[4 * ks + 1], fa[4 * ks + 2], fa[4 * ks + 3], dphi + ks * 16, ks);
      wg_commit();
      wg_wait<0>();
      reg_fence(aq); reg_fence(fa);
      arrive_pair(BAR(B_KVFREE), lane);
      feature_map(aq, sc0, sc1, fq_p, fq_m);
    }
    if (tid == 0) TSTAMP(4);
    ROLE_A();
    if (tid == 0) TSTAMP(5);
    {
      const int ui = tid < 252 ? tid : 0;
      const uint4* kp = a_kvf(P.arena) + bj * 512 + ui;
      uint32_t u[8];
      ld_units<2>(u, kp, 252);
      fix_units<2>(u, kp, 252, tag);
      const int rw = ui / 6, q = ui % 3, hh = rw < 40 ? rw >= 20 : rw - 40;
      const uint32_t base = sb + OFF_KVB + (rw >> 3) * 1536 + (rw & 7) * 16 + (hh * 2 + ((ui / 3) & 1)) * 4;
      if (tid < 252) {
#pragma unroll
        for (int i = 0; i < 2; i++) {
          const uint32_t bs = base + i * (9216 + 128) + q * 512;
          sts32(bs + (q == 2 ? 128 : 0), u[4 * i]);
          sts32(bs + 128 + (q >= 1 ? 128 : 0), u[4 * i + 1]);
          if (q < 2) { sts32(bs + 256 + q * 128, u[4 * i + 2]); sts32(bs + 384 + q * 128, u[4 * i + 3]); }
        }
      }
      fence_async_smem();
      bar_sync_c<1, 256>();
    }
    if (tid == 0) TSTAMP(18);
    {
      float ca[24], cb[24], c[40];
      reg_fence(ca); reg_fence(cb); reg_fence(fq_p); reg_fence(fq_m);
      const uint64_t dk = mk_desc(sb + OFF_KVB, 128, 1536, 0);
      wg_fence();
#pragma unroll
      for (int ks = 0; ks < 3; ks++) {
        wgmma_rs_n48<0>(ca, fq_p[4 * ks], fq_p[4 * ks + 1], fq_p[4 * ks + 2], fq_p[4 * ks + 3], dk + ks * 16, ks);
        wgmma_rs_n48<0>(cb, fq_p[4 * ks + 8], fq_p[4 * ks + 9], fq_p[4 * ks + 10], fq_p[4 * ks + 11], dk + 576 + ks * 16, ks);
      }
#pragma unroll
      for (int ks = 0; ks < 3; ks++) {
        wgmma_rs_n48<0>(ca, fq_m[4 * ks], fq_m[4 * ks + 1], fq_m[4 * ks + 2], fq_m[4 * ks + 3], dk + (3 + ks) * 16, 1);
        wgmma_rs_n48<0>(cb, fq_m[4 * ks + 8], fq_m[4 * ks + 9], fq_m[4 * ks + 10], fq_m[4 * ks + 11], dk + 576 + (3 + ks) * 16, 1);
      }
      wg_commit();
      wg_wait<0>();
      reg_fence(ca); reg_fence(cb); reg_fence(fq_p); reg_fence(fq_m);
      if (tid == 0) TSTAMP(19);
#pragma unroll
      for (int r = 0; r < 2; r++) {
        const int q0 = lane & ~3;
        const float r0 = __shfl_sync(~0u, rcp(ca[20 + 2 * r] + 1e-6f), q0), r1 = __shfl_sync(~0u, rcp(ca[21 + 2 * r] + 1e-6f), q0);
        const float r2 = __shfl_sync(~0u, rcp(cb[20 + 2 * r] + 1e-6f), q0), r3 = __shfl_sync(~0u, rcp(cb[21 + 2 * r] + 1e-6f), q0);
        const float s01 = lowt ? r0 : r1, s23 = lowt ? r2 : r3;
#pragma unroll
        for (int n = 0; n < 5; n++) {
          const float sa = n < 2 ? r0 : n == 2 ? s01 : r1, sc = n < 2 ? r2 : n == 2 ? s23 : r3;
          c[4 * n + 2 * r] = ca[4 * n + 2 * r] * sa; c[4 * n + 2 * r + 1] = ca[4 * n + 2 * r + 1] * sa;
          c[20 + 4 * n + 2 * r] = cb[4 * n + 2 * r] * sc; c[20 + 4 * n + 2 * r + 1] = cb[4 * n + 2 * r + 1] * sc;
        }
      }
      if (ORS) mbar_wait(BAR(B_HZ));
      uint4* dst = a_of(P.arena, bi) + (warp * 40 + bj * 5) * 32 + lane;
      uint32_t w[20];
#pragma unroll
      for (int n = 0; n < 20; n++) w[n] = (n & 3) ? pack_bf16(c[2 * n], c[2 * n + 1]) : pack_tag(c[2 * n], c[2 * n + 1], tag16);
#pragma unroll
      for (int u = 0; u < 5; u++) st_unit(dst + u * 32, w[4 * u], w[4 * u + 1], w[4 * u + 2], w[4 * u + 3]);
      st_hint_if(a_hint_o(P.arena, bi) + (warp * 8 + bj) * OHS, e1, lane == 0);

    }
    if (tid == 0) TSTAMP(6);
    uint32_t cf;
    asm volatile("ld.shared.u32 %0, [%1];" : "=r"(cf) : "r"(BAR(B_COUNT) + 4) : "memory");
    const int rank = cf & 1, fi = (cf >> 5) * 4 + ((cf >> 1) & 3), fp = ((cf >> 3) & 1) * 2 + ((cf >> 4) & 1), fj = fp * 2 + rank, cta = cf;
    const bool wide = fj < 6;
    const uint4* hp = a_hf(P.arena, fi) + (warp * 40) * 32 + lane;
    {
      const int half = bj >> 2;
      const uint4* op = a_of(P.arena, bi) + ((half * 4 + wq) * 40) * 32 + lane;
      float c[80], hh[40];
      uint32_t a[80];
      const uint4* ap = op + wg * 128;
      hint_wait<0>(a_hint_o(P.arena, bi) + ((half * 4 + wq) * 8 + (lane & 7)) * OHS, lane, e1, 0xff);
      if (tid == 0) TSTAMP(33);
#pragma unroll
      for (int r = 0; r < 5; r++) ld_units<4>(a + 16 * r, ap + r * 256, 32);
      reg_fence(c);
      const uint64_t dw = mk_desc(sb, 2048, 512, 2);
#pragma unroll
      for (int r = 0; r < 5; r++) {
        fix_units<4>(a + 16 * r, ap + r * 256, 32, tag);
        mbar_wait(BAR(B_FW + 2 * r) + wg * 8);
        const uint64_t d = dw + ((wg ? wo_off(2 * r + 1) : wo_off(2 * r)) >> 4);
#pragma unroll
        for (int i = 0; i < 16; i++) asm volatile("" : "+r"(a[16 * r + i])::"memory");
        wg_fence();
#pragma unroll
        for (int kk = 0; kk < 4; kk++)
          wgmma_rs_n160<1>(c, a[16 * r + 4 * kk], a[16 * r + 4 * kk + 1], a[16 * r + 4 * kk + 2], a[16 * r + 4 * kk + 3], d + (kk >> 1) * 640 + (kk & 1) * 64, r | kk);
        wg_commit();
        if (r == 0) { arrive_pair(BAR(B_EW + 0), lane); if (tid == 0) TSTAMP(7); }
        if (r >= 3) { wg_wait<1>(); arrive_pair(BAR(B_EW + r - 2), lane); }
      }
      mbar_wait(BAR(B_FX));
      mbar_wait(BAR(B_HZ));
      uint32_t xr[20];
#pragma unroll
      for (int u = 0; u < 5; u++) {
        const int oct = wg * 10 + 2 * u + smOct, r = wq * 16 + (lane & 15);
        ldsm4(sb + OFF_XT + (oct >> 2) * 4 * KB + r * 64 + (((oct & 3) ^ ((lane >> 1) & 3)) << 4), xr[4 * u], xr[4 * u + 1], xr[4 * u + 2], xr[4 * u + 3]);
      }
      wg_wait<0>();
      reg_fence(c); reg_fence(a);
      if (tid == 0) TSTAMP(8);
      {
        const uint32_t xo = sb + 40 * KB + (tid & 127) * 16;
        if (wg == 0) {
          bar_sync_c<2, 128>();
#pragma unroll
          for (int i = 0; i < 10; i++) sts128(xo + 20 * KB + i * 2048, __float_as_uint(c[40 + 4 * i]), __float_as_uint(c[41 + 4 * i]), __float_as_uint(c[42 + 4 * i]), __float_as_uint(c[43 + 4 * i]));
        } else {
          bar_sync_c<3, 128>();
#pragma unroll
          for (int i = 0; i < 10; i++) sts128(xo + i * 2048, __float_as_uint(c[4 * i]), __float_as_uint(c[4 * i + 1]), __float_as_uint(c[4 * i + 2]), __float_as_uint(c[4 * i + 3]));
        }
        if (wg == 0) {
#pragma unroll
          for (int n = 0; n < 20; n++) { hh[2 * n] = c[2 * n] + bf_lo(xr[n]); hh[2 * n + 1] = c[2 * n + 1] + bf_hi(xr[n]); }
        } else {
#pragma unroll
          for (int n = 0; n < 20; n++) { hh[2 * n] = c[40 + 2 * n] + bf_lo(xr[n]); hh[2 * n + 1] = c[41 + 2 * n] + bf_hi(xr[n]); }
        }
        bar_sync_c<1, 256>();
#pragma unroll
        for (int i = 0; i < 10; i++) {
          const uint4 v = lds128(xo + wg * 20 * KB + i * 2048);
          hh[4 * i] += __uint_as_float(v.x); hh[4 * i + 1] += __uint_as_float(v.y); hh[4 * i + 2] += __uint_as_float(v.z); hh[4 * i + 3] += __uint_as_float(v.w);
        }
      }
      uint4* dst = a_hf(P.arena, bi) + ((half * 4 + wq) * 40 + (bj & 3) * 10 + wg * 5) * 32 + lane;
#pragma unroll
      for (int u = 0; u < 5; u++)
        st_unit(dst + u * 32, pack_tag(hh[8 * u], hh[8 * u + 1], tag16), pack_bf16(hh[8 * u + 2], hh[8 * u + 3]), pack_bf16(hh[8 * u + 4], hh[8 * u + 5]), pack_bf16(hh[8 * u + 6], hh[8 * u + 7]));
      arrive_pair(BAR(B_EW + 3), lane);
      {
        float m[2], q[2];
#pragma unroll
        for (int r = 0; r < 2; r++) {
          const float k0 = __shfl_sync(~0u, hh[2 * r], lane & ~3);
          float s1 = 0.f, s2 = 0.f, q1 = 0.f, q2 = 0.f;
#pragma unroll
          for (int n = 0; n < 10; n++) {
            const float p = hh[4 * n + 2 * r] - k0, o = hh[4 * n + 2 * r + 1] - k0;
            s1 += p; s2 += o; q1 = fmaf(p, p, q1); q2 = fmaf(o, o, q2);
          }
          const float sm = quad_sum(s1 + s2), mu = sm * (1.f / 80.f);
          m[r] = k0 + mu;
          q[r] = fmaxf(quad_sum(q1 + q2) - sm * mu, 0.f);
        }
        if (t == 0) st_unit(a_hst(P.arena, bi) + (((half * 4 + wq) * 8 + (bj & 3) * 2 + wg) * 8) + g, (__float_as_uint(m[0]) & ~1u) | tag,
                            __float_as_uint(q[0]), __float_as_uint(m[1]), __float_as_uint(q[1]));
      }
    }
    if (tid == 0) TSTAMP(9);
    uint32_t fa[56];
    {
      float c[112];
      uint32_t h0[16], h1[16], h2[16], nm0, nm1;
      if (tid == 0) TSTAMP(34);
      {
        const uint4* sp = a_hst(P.arena, fi) + (warp * 8 + 2 * t) * 8 + g;
        uint32_t u[8];
        ld_units<2>(u, sp, 8);
        ld_units<4>(h0, hp, 32); ld_units<4>(h1, hp + 4 * 32, 32);
        while (__any_sync(~0u, ((u[0] ^ tag) | (u[4] ^ tag) | (h0[0] ^ tag) | (h0[4] ^ tag) | (h0[8] ^ tag) | (h0[12] ^ tag)) & 1)) {
          ld_units<2>(u, sp, 8); ld_units<4>(h0, hp, 32);
        }
        float mean[2], rs[2];
#pragma unroll
        for (int r = 0; r < 2; r++) {
          const float ma = __uint_as_float(u[2 * r]), mb = __uint_as_float(u[4 + 2 * r]);
          mean[r] = quad_sum(ma + mb) * 0.125f;
          const float da = ma - mean[r], db = mb - mean[r];
          const float m2 = quad_sum(__uint_as_float(u[2 * r + 1]) + __uint_as_float(u[5 + 2 * r]) + 80.f * (da * da + db * db));
          rs[r] = rsqrtf(m2 * (1.f / 640.f) + 1e-5f);
        }
        rstd0 = rs[0]; rstd1 = rs[1];
        if (t == 0) sts64f(sb + OFF_CS + (warp * 8 + g) * 8, rstd0, rstd1);
        nm0 = pack_bf16(-mean[0], -mean[0]); nm1 = pack_bf16(-mean[1], -mean[1]);
      }
      reg_fence(c);
      auto stepF = [&](uint32_t (&x)[16], uint32_t (&nx)[16], int kb) {
        fix_units<4>(x, hp + kb * 128, 32, tag);
        if (kb == 0) arrive_pair(BAR(B_HGO), lane);
#pragma unroll
        for (int i = 0; i < 16; i++) asm("add.rn.bf16x2 %0, %0, %1;" : "+r"(x[i]) : "r"((i & 1) ? nm1 : nm0));
        mbar_wait(BAR(B_FF + kb));
        if (kb == 0 && tid == 0) TSTAMP(10);
        const uint64_t db = mk_desc(sb + ff_off(kb), 4 * KB, 1024, 1);
        reg_fence(x);
        wg_fence();
#pragma unroll
        for (int kk = 0; kk < 4; kk++) wgmma_rs_n224<1>(c, x[4 * kk], x[4 * kk + 1], x[4 * kk + 2], x[4 * kk + 3], db + (kk >> 1) * 1024 + (kk & 1) * 128, kb | kk);
        wg_commit();
        wg_wait<1>();
        reg_fence(nx);
        if (kb + 2 < 10) ld_units<4>(nx, hp + (kb + 2) * 128, 32);
        if (kb > 0) arrive_pair(BAR(B_EF + kb - 1), lane);
      };
#pragma unroll 1
      for (int kb = 0; kb < 12; kb += 3) {
        stepF(h0, h2, kb);
        if (kb == 9) break;
        stepF(h1, h0, kb + 1); stepF(h2, h1, kb + 2);
      }
      wg_wait<0>();
      reg_fence(c); reg_fence(h0); reg_fence(h1); reg_fence(h2);
      arrive_pair(BAR(B_EF + 9), lane);
      if (tid == 0) TSTAMP(11);
#pragma unroll
      for (int n = 0; n < 56; n++) {
        fa[n] = pack_relu(c[2 * n], c[2 * n + 1]);
        if (n >= 48 && !wide) fa[n] = 0;
      }
    }
    if (tid == 0) TSTAMP(12);
    {
      float c[32];
      reg_fence(fa); reg_fence(c);
      uint4* const pbase = a_part(P.arena, fi) + wg * 4 * 128 + (tid & 127);
      uint32_t* const hbase = a_hint_p(P.arena, fi) + warp * 8;
      auto land = [&](int r) { return sb + warp * 2048 + lane * 16 + (r == 0 ? OFF_X : (uint32_t)(r - 1) * 16 * KB); };
      auto part = [&](int k) { return pbase + (fj * 4 + ((fp - 1 - k) & 3)) * 1024; };
      auto issue = [&](int s) {
        mbar_wait(BAR(B_FG + s));
        const uint64_t db = mk_desc(sb + f2_off(s), 28 * KB, 1024, 1);
        if (F2_PP) asm volatile("bar.sync %0, 256;" ::"r"(2 + wg) : "memory");
        wg_fence();
#pragma unroll
        for (int ks = 0; ks < 14; ks++) wgmma_rs_n64<1>(c, fa[4 * ks], fa[4 * ks + 1], fa[4 * ks + 2], fa[4 * ks + 3], db + ks * 128, ks);
        wg_commit();
        if (F2_PP && (s < 9 || wg == 0)) asm volatile("bar.arrive %0, 256;" ::"r"(3 - wg) : "memory");
      };
      auto request = [&](int k) {
        const uint4* p = part(k);
        const uint32_t d = land(k);
#pragma unroll
        for (int q = 0; q < 4; q++) asm volatile("cp.async.cg.shared.global [%0], [%1], 16;" ::"r"(d + q * 512), "l"(p + q * 128) : "memory");
        asm volatile("cp.async.commit_group;" ::: "memory");
      };
      auto fetch = [&](uint32_t (&w)[16], uint32_t d) {
#pragma unroll
        for (int q = 0; q < 4; q++) { const uint4 v = lds128(d + q * 512); w[4 * q] = v.x; w[4 * q + 1] = v.y; w[4 * q + 2] = v.z; w[4 * q + 3] = v.w; }
      };
      if (F2_PP && wg == 1) asm volatile("bar.arrive 2, 256;" ::: "memory");
      uint32_t hr[16], hv = 0;
      float gs[32];
      ld_units<4>(hr, hp + fj * 128, 32);
      issue(0);
#pragma unroll 1
      for (int r = 0;; r++) {
        uint32_t w[16];
        wg_wait<0>();
        reg_fence(c);
#pragma unroll
        for (int n = 0; n < 16; n++) w[n] = pack_bf16(c[2 * n], c[2 * n + 1]);
        if (r == 1) { mbar_wait(BAR(B_EF + 8)); mbar_wait(BAR(B_EF + 9)); }
        {
          uint32_t ra, rb;
          asm volatile("mapa.shared::cluster.u32 %0, %1, %2;" : "=r"(ra) : "r"(land(r)), "r"(rank ^ 1));
          asm volatile("mapa.shared::cluster.u32 %0, %1, %2;" : "=r"(rb) : "r"(BAR(B_DS + 2 * r + wg)), "r"(rank ^ 1));
#pragma unroll
          for (int q = 0; q < 4; q++)
            asm volatile("st.async.weak.shared::cluster.mbarrier::complete_tx::bytes.v4.b32 [%0], {%1, %2, %3, %4}, [%5];" ::"r"(ra + q * 512), "r"(w[4 * q]),
                         "r"(w[4 * q + 1]), "r"(w[4 * q + 2]), "r"(w[4 * q + 3]), "r"(rb) : "memory");
        }
        issue(2 * r + 1);
        if (tid == 0) TSTAMP2(50 + 2 * r);
        if (r == 4) break;
        arrive_if(BAR(B_EG + 2 * r), r < 3 && lane == 0);
        mbar_wait(BAR(B_DS + 2 * r + wg));
        fetch(w, land(r));
        wg_wait<0>();
        reg_fence(c);
#pragma unroll
        for (int n = 0; n < 16; n++) {
          const float lo = c[2 * n] + bf_lo(w[n]), hi = c[2 * n + 1] + bf_hi(w[n]);
          w[n] = (n & 3) ? pack_bf16(lo, hi) : pack_tag(lo, hi, tag16);
        }
        const int ch = f2_chunk(2 * r + 1, fp, rank);
        uint4* dst = pbase + (ch * 4 + fp) * 1024;
#pragma unroll
        for (int u = 0; u < 4; u++) st_unit(dst + u * 128, w[4 * u], w[4 * u + 1], w[4 * u + 2], w[4 * u + 3]);
        st_hint_if(hbase + ch * 64 + fp, e1, lane == 0);
        issue(2 * r + 2);
        arrive_if(BAR(B_EG + 2 * r + 1), r < 3 && lane == 0);
        if (r >= 2) request(r - 2);
        if (r == 3) {
          hv = ld_word(hbase + fj * 64 + ((fp - 3) & 3));
          asm volatile("cp.async.wait_group 1;" ::: "memory");
          fetch(w, land(0));
          fix_units<4>(w, part(0), 128, tag);
#pragma unroll
          for (int n = 0; n < 16; n++) { gs[2 * n] = bf_lo(w[n]); gs[2 * n + 1] = bf_hi(w[n]); }
        }
        if (tid == 0) TSTAMP2(51 + 2 * r);
      }
#pragma unroll 1
      for (int k = 1; k < 4; k++) {
        uint32_t w[16];
        if (k == 1) {
          while (hv != e1) hv = ld_word(hbase + fj * 64 + ((fp - 3) & 3));
          request(2);
          asm volatile("cp.async.wait_group 1;" ::: "memory");
        } else if (k == 2) mbar_wait(BAR(B_DS + 8 + wg));
        else asm volatile("cp.async.wait_group 0;" ::: "memory");
        fetch(w, land(k == 1 ? 1 : k == 2 ? 4 : 2));
        if (k != 2) fix_units<4>(w, part(k == 1 ? 1 : 2), 128, tag);
#pragma unroll
        for (int n = 0; n < 16; n++) { gs[2 * n] += bf_lo(w[n]); gs[2 * n + 1] += bf_hi(w[n]); }
        if (tid == 0) TSTAMP2(25 + k);
      }
      wg_wait<0>();
      reg_fence(c);
      reg_fence(fa);
#pragma unroll
      for (int n = 0; n < 16; n++) {
        const float rs = (n & 1) ? rstd1 : rstd0;
        c[2 * n] = fmaf(c[2 * n] + gs[2 * n], rs, bf_lo(hr[n])); c[2 * n + 1] = fmaf(c[2 * n + 1] + gs[2 * n + 1], rs, bf_hi(hr[n]));
      }
      if (tid == 0) TSTAMP(20);
      const uint32_t sa = sb + OFF_STG + warp * 2048;
      __syncwarp();
#pragma unroll
      for (int n = 0; n < 8; n += 2)
        stsm4(sa + (lane & 15) * 128 + (((n + smOct) ^ (lane & 7)) << 4), pack_bf16(c[4 * n], c[4 * n + 1]), pack_bf16(c[4 * n + 2], c[4 * n + 3]),
              pack_bf16(c[4 * n + 4], c[4 * n + 5]), pack_bf16(c[4 * n + 6], c[4 * n + 7]));
      fence_async_smem();
      __syncwarp();
      if (lane == 0) {
        tma_store2d(&P.out_st, sa, fj * 64, fi * 128 + warp * 16);
        bulk_commit();
        asm volatile("cp.async.bulk.wait_group.read 0;" ::: "memory");
        if (tid == 0) a_epoch(P.arena)[cta] = e1;
        if (tid == 0) TSTAMP(15);
        mbar_arrive(BAR(B_DONE));
      }
    }
  }
}

typedef CUresult (*EncodeFn)(CUtensorMap*, CUtensorMapDataType, cuuint32_t, void*, const cuuint64_t*, const cuuint64_t*, const cuuint32_t*,
                             const cuuint32_t*, CUtensorMapInterleave, CUtensorMapSwizzle, CUtensorMapL2promotion, CUtensorMapFloatOOBfill);

static void make_map(EncodeFn enc, CUtensorMap* tm, const void* base, int rank, const uint64_t* dims, const uint64_t* strides, const uint32_t* box,
                     CUtensorMapSwizzle sw) {
  cuuint64_t gd[3], gs[2]; cuuint32_t bd[3], es[3] = {1, 1, 1};
  for (int i = 0; i < rank; i++) { gd[i] = dims[i]; bd[i] = box[i]; }
  for (int i = 0; i + 1 < rank; i++) gs[i] = strides[i];
  enc(tm, CU_TENSOR_MAP_DATA_TYPE_BFLOAT16, rank, const_cast<void*>(base), gd, gs, bd, es, CU_TENSOR_MAP_INTERLEAVE_NONE, sw,
      CU_TENSOR_MAP_L2_PROMOTION_L2_128B, CU_TENSOR_MAP_FLOAT_OOB_FILL_NONE);
}

}

extern "C" void kernel_launch(void* const* d_in, const int* in_sizes, int n_in, void* d_out, int out_size) {
  using namespace hh;
  (void)in_sizes; (void)n_in; (void)out_size;
  void* fn = nullptr;
  cudaDriverEntryPointQueryResult qr;
  cudaGetDriverEntryPoint("cuTensorMapEncodeTiled", &fn, cudaEnableDefault, &qr);
  EncodeFn enc = (EncodeFn)fn;
  Params P;
  P.px = (const __nv_bfloat16*)d_in[0]; P.pwqkv = (const __nv_bfloat16*)d_in[1]; P.pwphi = (const __nv_bfloat16*)d_in[2];
  P.pwo = (const __nv_bfloat16*)d_in[3]; P.pw1 = (const __nv_bfloat16*)d_in[5]; P.pw2 = (const __nv_bfloat16*)d_in[6];
  void* arena;
  cudaGetSymbolAddress(&arena, g_arena);
  P.arena = (uint8_t*)(((uintptr_t)arena + PAGE - 1) & ~(uintptr_t)(PAGE - 1));
  const CUtensorMapSwizzle S128 = CU_TENSOR_MAP_SWIZZLE_128B, S32 = CU_TENSOR_MAP_SWIZZLE_32B;
  const uint64_t act_d[2] = {640, 2048}, act_s[1] = {1280};
  { const uint32_t b[2] = {64, 128}; make_map(enc, &P.x, P.px, 2, act_d, act_s, b, S128); }
  { const uint64_t d[3] = {32, 2048, 20}, s[2] = {1280, 64}; const uint32_t b[3] = {32, 64, 5}; make_map(enc, &P.xt, P.px, 3, d, s, b, CU_TENSOR_MAP_SWIZZLE_64B); }
  { const uint32_t b[2] = {64, 16}; make_map(enc, &P.out_st, d_out, 2, act_d, act_s, b, S128); }
  { const uint64_t d[3] = {640, 640, 3}, s[2] = {3840, 1280}; const uint32_t b[3] = {64, 32, 3}, bt[3] = {16, 32, 3};
    make_map(enc, &P.wqkv_main, P.pwqkv, 3, d, s, b, S128); make_map(enc, &P.wqkv_tail, P.pwqkv, 3, d, s, bt, S32); }
  { const uint64_t d[3] = {32, 640, 20}, s[2] = {1280, 64}; const uint32_t b[3] = {32, 32, 5}; make_map(enc, &P.wo, P.pwo, 3, d, s, b, CU_TENSOR_MAP_SWIZZLE_64B); }
  { const uint64_t d[3] = {1600, 640, 3}, s[2] = {3456, 128}; const uint32_t b[3] = {64, 32, 3}; make_map(enc, &P.w1_main, P.pw1, 3, d, s, b, S128); }
  { const uint64_t d[2] = {1728, 640}, s[1] = {3456}; const uint32_t b[2] = {32, 32}; make_map(enc, &P.w1_half, P.pw1, 2, d, s, b, S128); }
  { const uint64_t d[2] = {640, 1728}, s[1] = {1280}; const uint32_t b[2] = {64, 192}, bh[2] = {64, 32};
    make_map(enc, &P.w2_main, P.pw2, 2, d, s, b, S128); make_map(enc, &P.w2_half, P.pw2, 2, d, s, bh, S128); }

  cudaFuncSetAttribute(fused_block_kernel<true>, cudaFuncAttributeMaxDynamicSharedMemorySize, SMEM_BYTES);
  cudaFuncSetAttribute(fused_block_kernel<false>, cudaFuncAttributeMaxDynamicSharedMemorySize, SMEM_BYTES);
  cudaLaunchConfig_t cfg = {};
  cfg.gridDim = dim3(128); cfg.blockDim = dim3(384); cfg.dynamicSmemBytes = SMEM_BYTES; cfg.stream = cudaStreamPerThread;
  cudaLaunchAttribute at[1];
  at[0].id = cudaLaunchAttributeClusterDimension; at[0].val.clusterDim.x = 2; at[0].val.clusterDim.y = 1; at[0].val.clusterDim.z = 1;
  cfg.attrs = at; cfg.numAttrs = 1;
  static int by_sm = -1;
  if (by_sm < 0) {
    int dev = 0, sms = 0, n[3] = {0, 0, 0};
    cudaGetDevice(&dev);
    cudaDeviceGetAttribute(&sms, cudaDevAttrMultiProcessorCount, dev);
    const int cs[3] = {2, 4, 8};
    for (int i = 0; i < 3; i++) {
      at[0].val.clusterDim.x = cs[i];
      if (cudaOccupancyMaxActiveClusters(&n[i], fused_block_kernel<true>, &cfg) != cudaSuccess) { n[i] = 0; cudaGetLastError(); }
    }
    at[0].val.clusterDim.x = 2;
    by_sm = HH_BY_SM && sms == 132 && n[0] == 66 && n[1] == 30 && n[2] == 15;
  }
  if (by_sm) { cfg.gridDim = dim3(132); cudaLaunchKernelEx(&cfg, fused_block_kernel<true>, P); }
  else cudaLaunchKernelEx(&cfg, fused_block_kernel<false>, P);
}
```
